```python
import torch

def _softmax(x, axis=-1):
    return torch.softmax(x, dim=axis)

def _gelu(x):
    return torch.nn.functional.gelu(x, approximate='tanh')

def _silu(x):
    return torch.nn.functional.silu(x)

def _sigmoid(x):
    return torch.sigmoid(x)

def _layernorm(x, axis=-1, eps=1e-05):
    m = x.mean(dim=axis, keepdim=True)
    v = x.var(dim=axis, keepdim=True, unbiased=False)
    return (x - m) / torch.sqrt(v + eps)

def _scatter_add(tgt, idx, src, axis=0):
    return tgt.clone().index_add_(axis, idx, src)

def _segment_sum(src, seg, n):
    out = torch.zeros((n,) + src.shape[1:], dtype=src.dtype)
    return out.index_add_(0, seg, src)

def _pad(x, pw):
    flat = tuple((v for pair in reversed(pw) for v in pair))
    return torch.nn.functional.pad(x, flat)
kernel_name = 'adaLN_cond__gqa_block_cached__geglu_ffn__decode'

def setup_inputs():

    _w = lambda a: (lambda t: t.to(torch.bfloat16) if t.is_floating_point() else t)(torch.as_tensor(a))

    def _A_setup():
        B, Sq, D = (4, 1, 640)
        Hq, Hkv, Sk, Dh = (32, 32, 4096, 192)
        assert Hq % Hkv == 0, (Hq, Hkv)
        return {'x': _w((lambda *s: torch.randn(*s, dtype=torch.bfloat16) * 0.05)(B, Sq, D)), 'k_cache': _w((lambda *s: torch.randn(*s, dtype=torch.bfloat16) * 3.2)(B, Hkv, Sk, Dh)), 'v_cache': _w((lambda *s: torch.randn(*s, dtype=torch.bfloat16) * 0.4)(B, Hkv, Sk, Dh)), 'wq': _w((lambda *s: torch.randn(*s, dtype=torch.bfloat16) * 3.2)(D, Hq * Dh) * D ** (-0.5)), 'wo': _w((lambda *s: torch.randn(*s, dtype=torch.bfloat16) * 0.4)(Hq * Dh, D) * (Hq * Dh) ** (-0.5))}
    _A_in = _A_setup()

    def _B_setup():
        B, S, D, F = (4, 1, 640, 1536)
        return {'x': _w((lambda *s: torch.randn(*s, dtype=torch.bfloat16) * 0.05)(B, S, D)), 'w_gate': _w((lambda *s: torch.randn(*s, dtype=torch.bfloat16) * 0.05)(D, F)), 'w_up': _w((lambda *s: torch.randn(*s, dtype=torch.bfloat16) * 0.05)(D, F)), 'w_down': _w((lambda *s: torch.randn(*s, dtype=torch.bfloat16) * 0.05)(F, D))}
    _B_in = _B_setup()
    return {'A_x': _A_in['x'], 'A_k_cache': _A_in['k_cache'], 'A_v_cache': _A_in['v_cache'], 'A_wq': _A_in['wq'], 'A_wo': _A_in['wo'], 'B_x': _B_in['x'], 'B_w_gate': _B_in['w_gate'], 'B_w_up': _B_in['w_up'], 'B_w_down': _B_in['w_down'], 'c': _w((lambda *s: torch.randn(*s, dtype=torch.bfloat16) * 0.1)(4, 640) * 8.0), 'w_mod': _w((lambda *s: torch.randn(*s, dtype=torch.bfloat16) * 0.1)(640, 6 * 640) * 640 ** (-0.5) * 8.0)}

def reference(A_x, A_k_cache, A_v_cache, A_wq, A_wo, B_x, B_w_gate, B_w_up, B_w_down, c, w_mod):

    def _A_ref(x, k_cache, v_cache, wq, wo):
        B, Sq, D = x.shape
        Hq, Dh = (32, 192)
        Hkv = k_cache.shape[1]
        rep = Hq // Hkv
        q = (lambda x, *d: x.permute(*d))((x @ wq).reshape(B, Sq, Hq, Dh), 0, 2, 1, 3)
        k = (lambda x, n, axis: torch.repeat_interleave(x, n, dim=axis))(k_cache, rep, axis=1)
        v = (lambda x, n, axis: torch.repeat_interleave(x, n, dim=axis))(v_cache, rep, axis=1)
        scores = torch.einsum('bhqd,bhkd->bhqk', q, k) * Dh ** (-0.5)
        p = _softmax(scores, axis=-1)
        o = torch.einsum('bhqk,bhkd->bhqd', p, v)
        return (lambda x, *d: x.permute(*d))(o, 0, 2, 1, 3).reshape(B, Sq, Hq * Dh) @ wo

    def _B_ref(x, w_gate, w_up, w_down):
        return _gelu(x @ w_gate) * (x @ w_up) @ w_down
    x = A_x
    mod = (_silu(c) @ w_mod).reshape(c.shape[0], 6, 1, -1)
    sa, ca, ga, sb, cb, gb = (mod[:, 0].clone(), mod[:, 1].clone(), mod[:, 2].clone(), mod[:, 3].clone(), mod[:, 4].clone(), mod[:, 5].clone())
    h = _layernorm(x, axis=-1) * (1 + ca) + sa
    x = x + ga * _A_ref(h, A_k_cache, A_v_cache, A_wq, A_wo)
    h = _layernorm(x, axis=-1) * (1 + cb) + sb
    x = x + gb * _B_ref(h, B_w_gate, B_w_up, B_w_down)
    return x
```

```cpp
#include <cuda_runtime.h>
#include <cuda_bf16.h>
#include <stdint.h>

namespace {

constexpr int kB = 4, kD = 640, kH = 32, kSK = 4096, kDH = 192, kF = 1536;
constexpr int kNCTA = 128;
constexpr int kTileKeys = 64;
constexpr int kTileBytes = kTileKeys * kDH * 2;
constexpr int kNST = 8;
constexpr int kNCW = 8;
constexpr int kNCT = kNCW * 32;
constexpr int kThreads = kNCT + 32;
constexpr int kKTiles = kSK / kTileKeys;
constexpr int kWoRows = 16;
constexpr int kWoStages = kDH / kWoRows;
constexpr int kWoStageBytes = kWoRows * kD * 2;
constexpr int kNModCTA = 120;
constexpr int kNModA = 40;
constexpr int kNQCTA = 96;
constexpr int kNFCTA = 96;

constexpr int kOffRing = 0;
constexpr int kOffScores = kNST * kTileBytes;
constexpr int kOffVec = kOffScores + kSK * 4;
constexpr int kOffX1 = kOffRing + 32768;
constexpr int kOffSmall = kOffVec + kB * kD * 4;
constexpr int kOffBar = kOffSmall + 1024;
constexpr int kSmemBytes = kOffBar + 256;

__device__ float g_mod[kB * 6 * kD];
__device__ float g_q[kB * kH * kDH];
__device__ __align__(16) float g_y[kB * kD];
__device__ __align__(16) float g_out[kB * kD];
__device__ unsigned g_cnt[64 * 32];

constexpr int kCntModA = 0, kCntModB = 1, kCntY = 2, kCntOut = 3, kCntQ = 4;

__device__ __forceinline__ float bf16r(float x) { return __bfloat162float(__float2bfloat16_rn(x)); }
__device__ __forceinline__ float bflo(uint32_t u) { return __uint_as_float(u << 16); }
__device__ __forceinline__ float bfhi(uint32_t u) { return __uint_as_float(u & 0xffff0000u); }

__device__ __forceinline__ void mbar_init(uint32_t bar, uint32_t count) {
  asm volatile("mbarrier.init.shared::cta.b64 [%0], %1;" ::"r"(bar), "r"(count) : "memory");
}
__device__ __forceinline__ void mbar_expect_tx(uint32_t bar, uint32_t bytes) {
  asm volatile("mbarrier.arrive.expect_tx.shared::cta.b64 _, [%0], %1;" ::"r"(bar), "r"(bytes) : "memory");
}
__device__ __forceinline__ void mbar_arrive(uint32_t bar) {
  asm volatile("mbarrier.arrive.shared::cta.b64 _, [%0];" ::"r"(bar) : "memory");
}
__device__ __forceinline__ void mbar_wait(uint32_t bar, uint32_t parity) {
  uint32_t ok;
  int it = 0;
  do {
    asm volatile(
        "{ .reg .pred p; mbarrier.try_wait.parity.shared::cta.b64 p, [%1], %2; selp.u32 %0, 1, 0, p; }"
        : "=r"(ok)
        : "r"(bar), "r"(parity)
        : "memory");
    if (++it > (1 << 22)) __trap();
  } while (!ok);
}
__device__ __forceinline__ void bulk_load(uint32_t dst, const void* src, uint32_t bytes, uint32_t bar,
                                          uint64_t policy) {
  asm volatile(
      "cp.async.bulk.shared::cluster.global.mbarrier::complete_tx::bytes.L2::cache_hint [%0], [%1], %2, [%3], %4;" ::"r"(dst),
      "l"(src), "r"(bytes), "r"(bar), "l"(policy)
      : "memory");
}
__device__ __forceinline__ void cbar() { asm volatile("bar.sync 1, 256;" ::: "memory"); }

__device__ __forceinline__ unsigned ld_acquire(const unsigned* p) {
  unsigned v;
  asm volatile("ld.acquire.gpu.global.u32 %0, [%1];" : "=r"(v) : "l"(p) : "memory");
  return v;
}
__device__ __forceinline__ void wait_cnt(int idx, unsigned target) {
  const unsigned* p = &g_cnt[idx * 32];
  int it = 0;
  while (ld_acquire(p) < target) {
    if (++it > (1 << 24)) __trap();
  }
}
__device__ __forceinline__ void signal_cnt(int idx) {
  __threadfence();
  asm volatile("red.release.gpu.global.add.u32 [%0], 1;" ::"l"(&g_cnt[idx * 32]) : "memory");
}
__device__ __forceinline__ void red_add_v4(float* p, float a, float b, float c, float d) {
  asm volatile("red.global.add.v4.f32 [%0], {%1, %2, %3, %4};" ::"l"(p), "f"(a), "f"(b), "f"(c), "f"(d)
               : "memory");
}
__device__ __forceinline__ uint4 lds128(uint32_t addr) {
  uint4 v;
  asm volatile("ld.shared.v4.u32 {%0, %1, %2, %3}, [%4];" : "=r"(v.x), "=r"(v.y), "=r"(v.z), "=r"(v.w) : "r"(addr));
  return v;
}
__device__ __forceinline__ uint2 lds64(uint32_t addr) {
  uint2 v;
  asm volatile("ld.shared.v2.u32 {%0, %1}, [%2];" : "=r"(v.x), "=r"(v.y) : "r"(addr));
  return v;
}

template <int N>
__device__ __forceinline__ void halve(float (&v)[N], int mask, int lane) {
  const bool upper = (lane & mask) != 0;
#pragma unroll
  for (int i = 0; i < N / 2; i++) {
    float send = upper ? v[i] : v[i + N / 2];
    float keep = upper ? v[i + N / 2] : v[i];
    v[i] = keep + __shfl_xor_sync(0xffffffffu, send, mask);
  }
}

__device__ __forceinline__ void fma8(float* acc, uint4 w, float s) {
  acc[0] += s * bflo(w.x); acc[1] += s * bfhi(w.x);
  acc[2] += s * bflo(w.y); acc[3] += s * bfhi(w.y);
  acc[4] += s * bflo(w.z); acc[5] += s * bfhi(w.z);
  acc[6] += s * bflo(w.w); acc[7] += s * bfhi(w.w);
}

__device__ __forceinline__ float gelu_tanh(float x) {
  const float k0 = 0.7978845608028654f, k1 = 0.044715f;
  float inner = k0 * (x + k1 * x * x * x);
  return 0.5f * x * (1.0f + tanhf(inner));
}

__device__ __forceinline__ void layernorm_row(float (&v)[20]) {
  float s = 0.f;
#pragma unroll
  for (int i = 0; i < 20; i++) s += v[i];
#pragma unroll
  for (int m = 16; m > 0; m >>= 1) s += __shfl_xor_sync(0xffffffffu, s, m);
  const float mean = s * (1.0f / kD);
  float q = 0.f;
#pragma unroll
  for (int i = 0; i < 20; i++) { float d = v[i] - mean; q += d * d; }
#pragma unroll
  for (int m = 16; m > 0; m >>= 1) q += __shfl_xor_sync(0xffffffffu, q, m);
  const float var = bf16r(q * (1.0f / kD));
  const float mb = bf16r(mean);
  const float sd = bf16r(sqrtf(bf16r(var + 1e-5f)));
#pragma unroll
  for (int i = 0; i < 20; i++) v[i] = bf16r(bf16r(v[i] - mb) / sd);
}

__global__ void __launch_bounds__(kThreads, 1)
fused_kernel(const __nv_bfloat16* __restrict__ x, const __nv_bfloat16* __restrict__ kc,
             const __nv_bfloat16* __restrict__ vc, const __nv_bfloat16* __restrict__ wq,
             const __nv_bfloat16* __restrict__ wo, const __nv_bfloat16* __restrict__ wg,
             const __nv_bfloat16* __restrict__ wu, const __nv_bfloat16* __restrict__ wd,
             const __nv_bfloat16* __restrict__ cvec, const __nv_bfloat16* __restrict__ wmod,
             __nv_bfloat16* __restrict__ out) {
  extern __shared__ __align__(1024) uint8_t smem[];
  const uint32_t sbase = (uint32_t)__cvta_generic_to_shared(smem);
  float* s_scores = reinterpret_cast<float*>(smem + kOffScores);
  float* s_vec = reinterpret_cast<float*>(smem + kOffVec);
  float* s_x1 = reinterpret_cast<float*>(smem + kOffX1);
  float* s_small = reinterpret_cast<float*>(smem + kOffSmall);
  const uint32_t bar_full = sbase + kOffBar;
  const uint32_t bar_empty = sbase + kOffBar + 8 * kNST;

  const int tid = threadIdx.x;
  const int warp = tid >> 5, lane = tid & 31;
  const int cta = blockIdx.x;
  const int bb = cta >> 5, hh = cta & 31;

  if (tid == 0) {
    for (int s = 0; s < kNST; s++) {
      mbar_init(bar_full + 8 * s, 1);
      mbar_init(bar_empty + 8 * s, kNCW);
    }
    asm volatile("fence.mbarrier_init.release.cluster;" ::: "memory");
  }
  __syncthreads();

  if (warp == kNCW) {
    if (lane == 0) {
      uint64_t pol_stream, pol_norm;
      asm volatile("createpolicy.fractional.L2::evict_first.b64 %0, 1.0;" : "=l"(pol_stream));
      asm volatile("createpolicy.fractional.L2::evict_normal.b64 %0, 1.0;" : "=l"(pol_norm));
      const uint8_t* kp = reinterpret_cast<const uint8_t*>(kc) + (size_t)cta * kSK * kDH * 2;
      const uint8_t* vp = reinterpret_cast<const uint8_t*>(vc) + (size_t)cta * kSK * kDH * 2;
      const uint8_t* wp = reinterpret_cast<const uint8_t*>(wo) + (size_t)hh * kDH * kD * 2;
      const int total = 2 * kKTiles + kWoStages;
      for (int it = 0; it < total; it++) {
        const int st = it % kNST;
        if (it >= kNST) mbar_wait(bar_empty + 8 * st, ((it / kNST) - 1) & 1);
        const uint32_t dst = sbase + kOffRing + st * kTileBytes;
        if (it < 2 * kKTiles) {
          const uint8_t* src = (it < kKTiles) ? kp + (size_t)it * kTileBytes : vp + (size_t)(it - kKTiles) * kTileBytes;
          mbar_expect_tx(bar_full + 8 * st, kTileBytes);
          bulk_load(dst, src, kTileBytes, bar_full + 8 * st, pol_stream);
        } else {
          const uint8_t* src = wp + (size_t)(it - 2 * kKTiles) * kWoStageBytes;
          mbar_expect_tx(bar_full + 8 * st, kWoStageBytes);
          bulk_load(dst, src, kWoStageBytes, bar_full + 8 * st, pol_norm);
        }
      }
    }
    return;
  }

  uint4 wm[10];
  if (cta < kNModCTA) {
    const uint4* p = reinterpret_cast<const uint4*>(wmod + (size_t)(tid >> 2) * (6 * kD) + cta * 32 + (tid & 3) * 8);
#pragma unroll
    for (int i = 0; i < 10; i++) wm[i] = __ldg(p + (size_t)i * 64 * (6 * kD) / 8);
  }
  uint4 wqr[20];
  if (cta < kNQCTA) {
    const uint4* p = reinterpret_cast<const uint4*>(wq + (size_t)(tid >> 3) * (kH * kDH) + cta * 64 + (tid & 7) * 8);
#pragma unroll
    for (int i = 0; i < 20; i++) wqr[i] = __ldg(p + (size_t)i * 32 * (kH * kDH) / 8);
  }
  for (int i = tid; i < kB * kD; i += kNCT) {
    float cv = __bfloat162float(cvec[i]);
    s_vec[i] = bf16r(cv / (1.0f + __expf(-cv)));
  }
  if (cta == 0) {
    for (int i = tid; i < kB * kD; i += kNCT) { g_y[i] = 0.f; g_out[i] = 0.f; }
  }
  cbar();
  if (cta < kNModCTA) {
    float acc[32];
#pragma unroll
    for (int i = 0; i < 32; i++) acc[i] = 0.f;
#pragma unroll
    for (int i = 0; i < 10; i++) {
      const int r = (tid >> 2) + 64 * i;
#pragma unroll
      for (int b = 0; b < 4; b++) fma8(acc + 8 * b, wm[i], s_vec[b * kD + r]);
    }
    halve(acc, 16, lane);
    {
      float (&a16)[16] = *reinterpret_cast<float(*)[16]>(acc);
      halve(a16, 8, lane);
      float (&a8)[8] = *reinterpret_cast<float(*)[8]>(acc);
      halve(a8, 4, lane);
    }
    const int b = ((lane >> 4) & 1) * 2 + ((lane >> 3) & 1);
    const int col = (lane & 3) * 8 + ((lane >> 2) & 1) * 4;
    float* red = s_scores + warp * 128 + b * 32 + col;
#pragma unroll
    for (int k = 0; k < 4; k++) red[k] = acc[k];
    cbar();
    if (tid < 128) {
      float s = 0.f;
#pragma unroll
      for (int w = 0; w < kNCW; w++) s += s_scores[w * 128 + tid];
      g_mod[(tid >> 5) * (6 * kD) + cta * 32 + (tid & 31)] = bf16r(s);
    }
    cbar();
    if (tid == 0) signal_cnt(cta < kNModA ? kCntModA : kCntModB);
  } else if (cta == 0) {
  }

  if (cta < kNQCTA) {
    float xv[20];
    if (warp < 4) {
#pragma unroll
      for (int i = 0; i < 20; i++) xv[i] = __bfloat162float(x[warp * kD + lane + 32 * i]);
      layernorm_row(xv);
    }
    if (tid == 0) wait_cnt(kCntModA, kNModA);
    cbar();
    if (warp < 4) {
#pragma unroll
      for (int i = 0; i < 20; i++) {
        const int d = lane + 32 * i;
        const float sa = __ldcg(&g_mod[warp * (6 * kD) + d]);
        const float ca = __ldcg(&g_mod[warp * (6 * kD) + kD + d]);
        s_vec[warp * kD + d] = bf16r(bf16r(xv[i] * bf16r(1.0f + ca)) + sa);
      }
    }
    cbar();
    float acc[32];
#pragma unroll
    for (int i = 0; i < 32; i++) acc[i] = 0.f;
#pragma unroll
    for (int i = 0; i < 20; i++) {
      const int r = (tid >> 3) + 32 * i;
#pragma unroll
      for (int b = 0; b < 4; b++) fma8(acc + 8 * b, wqr[i], s_vec[b * kD + r]);
    }
    halve(acc, 16, lane);
    {
      float (&a16)[16] = *reinterpret_cast<float(*)[16]>(acc);
      halve(a16, 8, lane);
    }
    const int b = ((lane >> 4) & 1) * 2 + ((lane >> 3) & 1);
    float* red = s_scores + warp * 256 + b * 64 + (lane & 7) * 8;
#pragma unroll
    for (int k = 0; k < 8; k++) red[k] = acc[k];
    cbar();
    {
      float s = 0.f;
#pragma unroll
      for (int w = 0; w < kNCW; w++) s += s_scores[w * 256 + tid];
      g_q[(tid >> 6) * (kH * kDH) + cta * 64 + (tid & 63)] = bf16r(s);
    }
    cbar();
    if (tid == 0) signal_cnt(kCntQ + cta / 3);
  }

  if (tid == 0) wait_cnt(kCntQ + hh, 3);
  cbar();
  const int j = lane & 7, g = lane >> 3;
  float qf[24];
#pragma unroll
  for (int i = 0; i < 3; i++)
#pragma unroll
    for (int e = 0; e < 8; e++) qf[i * 8 + e] = __ldcg(&g_q[bb * (kH * kDH) + hh * kDH + (j + 8 * i) * 8 + e]);

  uint4 wgr[5], wur[5];
  uint2 wdr[16];
  if (cta < kNFCTA) {
    const size_t off = (size_t)(tid >> 1) * kF + cta * 16 + (tid & 1) * 8;
    const uint4* pg = reinterpret_cast<const uint4*>(wg + off);
    const uint4* pu = reinterpret_cast<const uint4*>(wu + off);
#pragma unroll
    for (int i = 0; i < 5; i++) {
      wgr[i] = __ldg(pg + (size_t)i * 128 * kF / 8);
      wur[i] = __ldg(pu + (size_t)i * 128 * kF / 8);
    }
    if (tid < 160) {
      const uint2* pd = reinterpret_cast<const uint2*>(wd + (size_t)cta * 16 * kD + tid * 4);
#pragma unroll
      for (int r = 0; r < 16; r++) wdr[r] = __ldg(pd + r * kD / 4);
    }
  }

  const float scale = 0.07216878364870322f;
  float lmax = -INFINITY;
  int it = 0;
  for (; it < kKTiles; it++) {
    const int st = it % kNST;
    mbar_wait(bar_full + 8 * st, (it / kNST) & 1);
    const uint32_t base = sbase + kOffRing + st * kTileBytes + (warp * 8 + g) * (kDH * 2) + j * 16;
    uint4 kv[2][3];
#pragma unroll
    for (int u = 0; u < 2; u++)
#pragma unroll
      for (int i = 0; i < 3; i++) kv[u][i] = lds128(base + u * 4 * (kDH * 2) + i * 128);
    float sc[2];
#pragma unroll
    for (int u = 0; u < 2; u++) {
      float a0 = 0.f, a1 = 0.f;
#pragma unroll
      for (int i = 0; i < 3; i++) {
        a0 += qf[i * 8 + 0] * bflo(kv[u][i].x); a1 += qf[i * 8 + 1] * bfhi(kv[u][i].x);
        a0 += qf[i * 8 + 2] * bflo(kv[u][i].y); a1 += qf[i * 8 + 3] * bfhi(kv[u][i].y);
        a0 += qf[i * 8 + 4] * bflo(kv[u][i].z); a1 += qf[i * 8 + 5] * bfhi(kv[u][i].z);
        a0 += qf[i * 8 + 6] * bflo(kv[u][i].w); a1 += qf[i * 8 + 7] * bfhi(kv[u][i].w);
      }
      sc[u] = a0 + a1;
    }
    __syncwarp();
    if (lane == 0) mbar_arrive(bar_empty + 8 * st);
#pragma unroll
    for (int m = 1; m < 8; m <<= 1) {
      sc[0] += __shfl_xor_sync(0xffffffffu, sc[0], m);
      sc[1] += __shfl_xor_sync(0xffffffffu, sc[1], m);
    }
#pragma unroll
    for (int u = 0; u < 2; u++) {
      const float s = bf16r(bf16r(sc[u]) * scale);
      lmax = fmaxf(lmax, s);
      if (j == 0) s_scores[it * kTileKeys + warp * 8 + u * 4 + g] = s;
    }
  }
#pragma unroll
  for (int m = 16; m > 0; m >>= 1) lmax = fmaxf(lmax, __shfl_xor_sync(0xffffffffu, lmax, m));
  if (lane == 0) s_small[warp] = lmax;
  cbar();
  float gmax = s_small[0];
#pragma unroll
  for (int w = 1; w < kNCW; w++) gmax = fmaxf(gmax, s_small[w]);
  float ev[16];
  float lsum = 0.f;
#pragma unroll
  for (int i = 0; i < 16; i++) {
    ev[i] = __expf(s_scores[tid + kNCT * i] - gmax);
    lsum += ev[i];
  }
#pragma unroll
  for (int m = 16; m > 0; m >>= 1) lsum += __shfl_xor_sync(0xffffffffu, lsum, m);
  if (lane == 0) s_small[8 + warp] = lsum;
  cbar();
  float gsum = 0.f;
#pragma unroll
  for (int w = 0; w < kNCW; w++) gsum += s_small[8 + w];
  const float inv = 1.0f / gsum;
#pragma unroll
  for (int i = 0; i < 16; i++) s_scores[tid + kNCT * i] = bf16r(ev[i] * inv);
  cbar();

  float oa[24];
#pragma unroll
  for (int i = 0; i < 24; i++) oa[i] = 0.f;
  for (; it < 2 * kKTiles; it++) {
    const int st = it % kNST;
    mbar_wait(bar_full + 8 * st, (it / kNST) & 1);
    const uint32_t base = sbase + kOffRing + st * kTileBytes + (warp * 8 + g) * (kDH * 2) + j * 16;
    uint4 vv[2][3];
#pragma unroll
    for (int u = 0; u < 2; u++)
#pragma unroll
      for (int i = 0; i < 3; i++) vv[u][i] = lds128(base + u * 4 * (kDH * 2) + i * 128);
    float p[2];
#pragma unroll
    for (int u = 0; u < 2; u++) p[u] = s_scores[(it - kKTiles) * kTileKeys + warp * 8 + u * 4 + g];
#pragma unroll
    for (int u = 0; u < 2; u++)
#pragma unroll
      for (int i = 0; i < 3; i++) fma8(oa + 8 * i, vv[u][i], p[u]);
    __syncwarp();
    if (lane == 0) mbar_arrive(bar_empty + 8 * st);
  }
#pragma unroll
  for (int i = 0; i < 24; i++) {
    oa[i] += __shfl_xor_sync(0xffffffffu, oa[i], 8);
    oa[i] += __shfl_xor_sync(0xffffffffu, oa[i], 16);
  }
  cbar();
  if (g == 0) {
#pragma unroll
    for (int i = 0; i < 3; i++)
#pragma unroll
      for (int e = 0; e < 8; e++) s_scores[warp * kDH + (j + 8 * i) * 8 + e] = oa[i * 8 + e];
  }
  cbar();
  if (tid < kDH) {
    float s = 0.f;
#pragma unroll
    for (int w = 0; w < kNCW; w++) s += s_scores[w * kDH + tid];
    s_small[16 + tid] = bf16r(s);
  }
  cbar();

  float ya[20];
#pragma unroll
  for (int i = 0; i < 20; i++) ya[i] = 0.f;
  for (; it < 2 * kKTiles + kWoStages; it++) {
    const int st = it % kNST;
    const int ws = it - 2 * kKTiles;
    mbar_wait(bar_full + 8 * st, (it / kNST) & 1);
    const uint32_t base = sbase + kOffRing + st * kTileBytes + (warp * 2) * (kD * 2) + lane * 8;
    uint2 wv[2][5];
#pragma unroll
    for (int rr = 0; rr < 2; rr++)
#pragma unroll
      for (int i = 0; i < 5; i++) wv[rr][i] = lds64(base + rr * (kD * 2) + i * 256);
#pragma unroll
    for (int rr = 0; rr < 2; rr++) {
      const float ov = s_small[16 + ws * kWoRows + warp * 2 + rr];
#pragma unroll
      for (int i = 0; i < 5; i++) {
        ya[i * 4 + 0] += ov * bflo(wv[rr][i].x); ya[i * 4 + 1] += ov * bfhi(wv[rr][i].x);
        ya[i * 4 + 2] += ov * bflo(wv[rr][i].y); ya[i * 4 + 3] += ov * bfhi(wv[rr][i].y);
      }
    }
    __syncwarp();
    if (lane == 0) mbar_arrive(bar_empty + 8 * st);
  }
  cbar();
  {
    float4* red = reinterpret_cast<float4*>(smem + kOffRing) + warp * (kD / 4);
#pragma unroll
    for (int i = 0; i < 5; i++) red[lane + 32 * i] = make_float4(ya[i * 4], ya[i * 4 + 1], ya[i * 4 + 2], ya[i * 4 + 3]);
  }
  cbar();
  if (tid < kD / 4) {
    float4 s = make_float4(0.f, 0.f, 0.f, 0.f);
    const float4* red = reinterpret_cast<const float4*>(smem + kOffRing);
#pragma unroll
    for (int w = 0; w < kNCW; w++) {
      float4 v = red[w * (kD / 4) + tid];
      s.x += v.x; s.y += v.y; s.z += v.z; s.w += v.w;
    }
    red_add_v4(&g_y[bb * kD + tid * 4], s.x, s.y, s.z, s.w);
    __threadfence();
  }
  cbar();
  if (tid == 0) signal_cnt(kCntY);
  if (cta >= kNFCTA) return;

  if (tid == 0) { wait_cnt(kCntModB, kNModCTA - kNModA); wait_cnt(kCntY, kNCTA); }
  cbar();
  if (warp < 4) {
    float xv[20];
#pragma unroll
    for (int i = 0; i < 20; i++) {
      const int d = lane + 32 * i;
      const float y = bf16r(__ldcg(&g_y[warp * kD + d]));
      const float ga = __ldcg(&g_mod[warp * (6 * kD) + 2 * kD + d]);
      const float x0 = __bfloat162float(x[warp * kD + d]);
      xv[i] = bf16r(x0 + bf16r(ga * y));
      s_x1[warp * kD + d] = xv[i];
    }
    float sbv[20], cbv[20];
#pragma unroll
    for (int i = 0; i < 20; i++) {
      const int d = lane + 32 * i;
      sbv[i] = __ldcg(&g_mod[warp * (6 * kD) + 3 * kD + d]);
      cbv[i] = __ldcg(&g_mod[warp * (6 * kD) + 4 * kD + d]);
    }
    layernorm_row(xv);
#pragma unroll
    for (int i = 0; i < 20; i++)
      s_vec[warp * kD + lane + 32 * i] = bf16r(bf16r(xv[i] * bf16r(1.0f + cbv[i])) + sbv[i]);
  }
  cbar();
  {
    float acc[64];
#pragma unroll
    for (int i = 0; i < 64; i++) acc[i] = 0.f;
#pragma unroll
    for (int i = 0; i < 5; i++) {
      const int r = (tid >> 1) + 128 * i;
#pragma unroll
      for (int b = 0; b < 4; b++) {
        const float hv = s_vec[b * kD + r];
        fma8(acc + 8 * b, wgr[i], hv);
        fma8(acc + 32 + 8 * b, wur[i], hv);
      }
    }
    halve(acc, 16, lane);
    float (&a32)[32] = *reinterpret_cast<float(*)[32]>(acc);
    halve(a32, 8, lane);
    float (&a16)[16] = *reinterpret_cast<float(*)[16]>(acc);
    halve(a16, 4, lane);
    float (&a8)[8] = *reinterpret_cast<float(*)[8]>(acc);
    halve(a8, 2, lane);
    const int m = (lane >> 4) & 1;
    const int b = ((lane >> 3) & 1) * 2 + ((lane >> 2) & 1);
    const int col = (lane & 1) * 8 + ((lane >> 1) & 1) * 4;
    float* red = s_scores + warp * 128 + (m * 4 + b) * 16 + col;
#pragma unroll
    for (int k = 0; k < 4; k++) red[k] = acc[k];
  }
  cbar();
  if (tid < 64) {
    float gsum2 = 0.f, usum = 0.f;
#pragma unroll
    for (int w = 0; w < kNCW; w++) {
      gsum2 += s_scores[w * 128 + tid];
      usum += s_scores[w * 128 + 64 + tid];
    }
    const float gv = bf16r(gsum2), uv = bf16r(usum);
    s_small[256 + tid] = bf16r(bf16r(gelu_tanh(gv)) * uv);
  }
  cbar();
  if (tid < 160) {
    float acc[16];
#pragma unroll
    for (int i = 0; i < 16; i++) acc[i] = 0.f;
#pragma unroll
    for (int r = 0; r < 16; r++) {
      const float w0 = bflo(wdr[r].x), w1 = bfhi(wdr[r].x), w2 = bflo(wdr[r].y), w3 = bfhi(wdr[r].y);
#pragma unroll
      for (int b = 0; b < 4; b++) {
        const float a = s_small[256 + b * 16 + r];
        acc[b * 4 + 0] += a * w0; acc[b * 4 + 1] += a * w1; acc[b * 4 + 2] += a * w2; acc[b * 4 + 3] += a * w3;
      }
    }
#pragma unroll
    for (int b = 0; b < 4; b++)
      red_add_v4(&g_out[b * kD + tid * 4], acc[b * 4], acc[b * 4 + 1], acc[b * 4 + 2], acc[b * 4 + 3]);
    __threadfence();
  }
  cbar();
  if (tid == 0) {
    __threadfence();
    unsigned prev = atomicAdd(&g_cnt[kCntOut * 32], 1u);
    s_small[0] = (prev == kNFCTA - 1) ? 1.0f : 0.0f;
    __threadfence();
  }
  cbar();
  if (s_small[0] != 0.0f) {
    __threadfence();
    for (int i = tid; i < kB * kD; i += kNCT) {
      const int b = i / kD, d = i - b * kD;
      const float f = bf16r(__ldcg(&g_out[i]));
      const float gb = __ldcg(&g_mod[b * (6 * kD) + 5 * kD + d]);
      out[i] = __float2bfloat16_rn(s_x1[i] + bf16r(gb * f));
    }
    if (tid < kCntQ + kH) g_cnt[tid * 32] = 0u;
  }
}

}

extern "C" void kernel_launch(void* const* d_in, const int* in_sizes, int n_in, void* d_out, int out_size) {
  const __nv_bfloat16* x = (const __nv_bfloat16*)d_in[0];
  const __nv_bfloat16* kc = (const __nv_bfloat16*)d_in[1];
  const __nv_bfloat16* vc = (const __nv_bfloat16*)d_in[2];
  const __nv_bfloat16* wq = (const __nv_bfloat16*)d_in[3];
  const __nv_bfloat16* wo = (const __nv_bfloat16*)d_in[4];
  const __nv_bfloat16* wg = (const __nv_bfloat16*)d_in[6];
  const __nv_bfloat16* wu = (const __nv_bfloat16*)d_in[7];
  const __nv_bfloat16* wd = (const __nv_bfloat16*)d_in[8];
  const __nv_bfloat16* cv = (const __nv_bfloat16*)d_in[9];
  const __nv_bfloat16* wmod = (const __nv_bfloat16*)d_in[10];
  static bool attr_done = false;
  if (!attr_done) {
    cudaFuncSetAttribute(fused_kernel, cudaFuncAttributeMaxDynamicSharedMemorySize, kSmemBytes);
    attr_done = true;
  }
  fused_kernel<<<kNCTA, kThreads, kSmemBytes>>>(x, kc, vc, wq, wo, wg, wu, wd, cv, wmod, (__nv_bfloat16*)d_out);
}
```

```cpp
#include <cuda_runtime.h>
#include <cuda_bf16.h>
#include <stdint.h>

namespace {

constexpr int kB = 4, kD = 640, kH = 32, kSK = 4096, kDH = 192, kF = 1536;
constexpr int kNCTA = 128;
constexpr int kTileKeys = 64;
constexpr int kTileBytes = kTileKeys * kDH * 2;
constexpr int kNST = 5;
#define KINFL 3
#define KS0 1
#define KS1 4
constexpr int kInflight = KINFL;
constexpr int kStart0 = KS0, kStart1 = KS1;
constexpr int kNCW = 8;
constexpr int kNCT = kNCW * 32;
constexpr int kThreads = kNCT + 128;
constexpr int kKTiles = kSK / kTileKeys;
constexpr int kTotTiles = 2 * kKTiles;
constexpr int kWoRows = 48;
constexpr int kWoPitch = kD * 2 + 32;
constexpr int kNModCTA = 120;
constexpr int kNQCTA = 96;
constexpr int kNFCTA = 96;
constexpr int kNDCTA = 40;

constexpr int kOffRing = 0;
constexpr int kOffWo = kNST * kTileBytes;
constexpr int kFreeSt = 2;
constexpr int kOffWq = kFreeSt * kTileBytes;
constexpr int kOffWmod = kOffWq + kD * 128;
constexpr int kOffScores = kOffWo + kWoRows * kWoPitch;
constexpr int kOffAct = kOffScores + kSK * 4;
constexpr int kActPitch = kF * 2 + 16;
constexpr int kOffSmall = kOffAct + kB * kActPitch;
constexpr int kOffXb = kOffSmall + 1024;
constexpr int kOffX1 = kOffXb + kB * kD * 2;
constexpr int kOffBar = kOffX1 + kB * kD * 4;
constexpr int kSmemBytes = kOffBar + 256;
static_assert(kSmemBytes <= 232448, "smem");
static_assert(kOffWmod + kD * 64 <= kOffWo + kWoRows * kWoPitch, "prologue weights");
static_assert(kOffWo % 128 == 0 && kOffScores % 16 == 0 && kOffAct % 16 == 0, "align");

#define STAMP(k)

__device__ unsigned long long g_modt[kB * 6 * kD / 2];
__device__ unsigned long long g_qt[kB * kH * kDH / 2];
__device__ unsigned long long g_ot[kH * kB * kDH / 2];
__device__ unsigned long long g_actt[kB * kF / 2];
__device__ __align__(16) float g_y[2][kB * kD];
__device__ unsigned g_cnt[32];
__device__ unsigned g_epoch;

constexpr int kCntY = 0;

__device__ __forceinline__ float bf16r(float x) { return __bfloat162float(__float2bfloat16_rn(x)); }
__device__ __forceinline__ float bflo(uint32_t u) { return __uint_as_float(u << 16); }
__device__ __forceinline__ float bfhi(uint32_t u) { return __uint_as_float(u & 0xffff0000u); }
__device__ __forceinline__ uint32_t pack_bf16(float lo, float hi) {
  __nv_bfloat162 v = __floats2bfloat162_rn(lo, hi);
  return *reinterpret_cast<uint32_t*>(&v);
}

__device__ __forceinline__ void mbar_init(uint32_t bar, uint32_t count) {
  asm volatile("mbarrier.init.shared::cta.b64 [%0], %1;" ::"r"(bar), "r"(count) : "memory");
}
__device__ __forceinline__ void mbar_expect_tx(uint32_t bar, uint32_t bytes) {
  asm volatile("mbarrier.arrive.expect_tx.shared::cta.b64 _, [%0], %1;" ::"r"(bar), "r"(bytes) : "memory");
}
__device__ __forceinline__ void mbar_arrive(uint32_t bar) {
  asm volatile("mbarrier.arrive.shared::cta.b64 _, [%0];" ::"r"(bar) : "memory");
}
__device__ __forceinline__ void mbar_wait(uint32_t bar, uint32_t parity) {
  uint32_t ok;
  int it = 0;
  do {
    asm volatile(
        "{ .reg .pred p; mbarrier.try_wait.parity.shared::cta.b64 p, [%1], %2; selp.u32 %0, 1, 0, p; }"
        : "=r"(ok)
        : "r"(bar), "r"(parity)
        : "memory");
    if (++it > (1 << 22)) __trap();
  } while (!ok);
}
__device__ __forceinline__ bool mbar_test(uint32_t bar, uint32_t parity) {
  uint32_t ok;
  asm volatile(
      "{ .reg .pred p; mbarrier.test_wait.parity.shared::cta.b64 p, [%1], %2; selp.u32 %0, 1, 0, p; }"
      : "=r"(ok)
      : "r"(bar), "r"(parity)
      : "memory");
  return ok != 0;
}
__device__ __forceinline__ void bulk_load(uint32_t dst, const void* src, uint32_t bytes, uint32_t bar,
                                          uint64_t policy) {
  asm volatile(
      "cp.async.bulk.shared::cluster.global.mbarrier::complete_tx::bytes.L2::cache_hint [%0], [%1], %2, [%3], %4;" ::"r"(dst),
      "l"(src), "r"(bytes), "r"(bar), "l"(policy)
      : "memory");
}
__device__ __forceinline__ void cbar() { asm volatile("bar.sync 1, 256;" ::: "memory"); }

__device__ __forceinline__ unsigned ld_acquire(const unsigned* p) {
  unsigned v;
  asm volatile("ld.acquire.gpu.global.u32 %0, [%1];" : "=r"(v) : "l"(p) : "memory");
  return v;
}
__device__ __forceinline__ void wait_cnt(int idx, unsigned target) {
  const unsigned* p = &g_cnt[idx * 32];
  int it = 0;
  while ((int)(ld_acquire(p) - target) < 0) {
    if (++it > (1 << 24)) break;
  }
}
__device__ __forceinline__ void signal_cnt(int idx) {
  asm volatile("red.release.gpu.global.add.u32 [%0], 1;" ::"l"(&g_cnt[idx * 32]) : "memory");
}
__device__ __forceinline__ void red_add_v4(float* p, float a, float b, float c, float d) {
  asm volatile("red.global.add.v4.f32 [%0], {%1, %2, %3, %4};" ::"l"(p), "f"(a), "f"(b), "f"(c), "f"(d)
               : "memory");
}
__device__ __forceinline__ void put_tagged(unsigned long long* p, uint32_t tag, uint32_t payload) {
  const unsigned long long v = ((unsigned long long)tag << 32) | payload;
  asm volatile("st.relaxed.gpu.global.u64 [%0], %1;" ::"l"(p), "l"(v) : "memory");
}
__device__ __forceinline__ unsigned long long ld_relaxed64(const unsigned long long* p) {
  unsigned long long v;
  asm volatile("ld.relaxed.gpu.global.u64 %0, [%1];" : "=l"(v) : "l"(p) : "memory");
  return v;
}
template <int N>
__device__ __forceinline__ void get_tagged(uint32_t (&val)[N], const unsigned long long* p, int stride, uint32_t tag,
                                           bool real = true) {
  int it = 0;
  bool ok;
  do {
    ok = true;
#pragma unroll
    for (int i = 0; i < N; i++) {
      const unsigned long long v = ld_relaxed64(p + i * stride);
      val[i] = (uint32_t)v;
      ok = ok && ((uint32_t)(v >> 32) == tag);
    }
    if (++it > (1 << 22)) __trap();
  } while (!ok && real);
}

__device__ __forceinline__ uint4 lds128(uint32_t addr) {
  uint4 v;
  asm volatile("ld.shared.v4.u32 {%0, %1, %2, %3}, [%4];" : "=r"(v.x), "=r"(v.y), "=r"(v.z), "=r"(v.w) : "r"(addr));
  return v;
}
__device__ __forceinline__ uint2 lds64(uint32_t addr) {
  uint2 v;
  asm volatile("ld.shared.v2.u32 {%0, %1}, [%2];" : "=r"(v.x), "=r"(v.y) : "r"(addr));
  return v;
}
__device__ __forceinline__ uint32_t lds32(uint32_t addr) {
  uint32_t v;
  asm volatile("ld.shared.u32 %0, [%1];" : "=r"(v) : "r"(addr));
  return v;
}
__device__ __forceinline__ uint4 ldg128(const void* p) {
  uint4 v;
  asm volatile("ld.global.nc.L1::no_allocate.v4.u32 {%0, %1, %2, %3}, [%4];"
               : "=r"(v.x), "=r"(v.y), "=r"(v.z), "=r"(v.w) : "l"(p));
  return v;
}
__device__ __forceinline__ uint2 ldg64(const void* p) {
  uint2 v;
  asm volatile("ld.global.nc.L1::no_allocate.v2.u32 {%0, %1}, [%2];" : "=r"(v.x), "=r"(v.y) : "l"(p));
  return v;
}
__device__ __forceinline__ uint32_t ldg32(const void* p) {
  uint32_t v;
  asm volatile("ld.global.nc.L1::no_allocate.u32 %0, [%1];" : "=r"(v) : "l"(p));
  return v;
}
__device__ __forceinline__ void cp_async16(uint32_t dst, const void* src) {
  asm volatile("cp.async.cg.shared.global [%0], [%1], 16;" ::"r"(dst), "l"(src) : "memory");
}

__device__ __forceinline__ void fma8(float* acc, uint4 w, float s) {
  acc[0] += s * bflo(w.x); acc[1] += s * bfhi(w.x);
  acc[2] += s * bflo(w.y); acc[3] += s * bfhi(w.y);
  acc[4] += s * bflo(w.z); acc[5] += s * bfhi(w.z);
  acc[6] += s * bflo(w.w); acc[7] += s * bfhi(w.w);
}

__device__ __forceinline__ float gelu_tanh(float x) {
  const float k0 = 0.7978845608028654f, k1 = 0.044715f;
  float inner = k0 * (x + k1 * x * x * x);
  float th = 1.0f - __fdividef(2.0f, 1.0f + __expf(2.0f * inner));
  return 0.5f * x * (1.0f + th);
}
__device__ __forceinline__ float sqrt_fast(float x) {
  float r;
  asm("sqrt.approx.f32 %0, %1;" : "=f"(r) : "f"(x));
  return r;
}

__device__ __forceinline__ void mma16816(float (&c)[4], uint32_t a0, uint32_t a2, uint32_t b0, uint32_t b1) {
  asm volatile(
      "mma.sync.aligned.m16n8k16.row.col.f32.bf16.bf16.f32 {%0,%1,%2,%3}, {%4,%5,%6,%7}, {%8,%9}, {%0,%1,%2,%3};"
      : "+f"(c[0]), "+f"(c[1]), "+f"(c[2]), "+f"(c[3])
      : "r"(a0), "r"(0u), "r"(a2), "r"(0u), "r"(b0), "r"(b1));
}
__device__ __forceinline__ int kperm(int k) {
  return (k & ~15) | (((k >> 3) & 1) << 3) | ((k & 3) << 1) | ((k >> 2) & 1);
}
__device__ __forceinline__ void mma_word(float (&lo)[4], float (&hi)[4], uint32_t a0, uint32_t a2, uint32_t w0,
                                         uint32_t w1, uint32_t w2, uint32_t w3) {
  mma16816(lo, a0, a2, __byte_perm(w0, w1, 0x5410), __byte_perm(w2, w3, 0x5410));
  mma16816(hi, a0, a2, __byte_perm(w0, w1, 0x7632), __byte_perm(w2, w3, 0x7632));
}
__device__ __forceinline__ void blk64(float (&acc)[8][4], uint32_t a0, uint32_t a2, const uint4 (&w)[4]) {
  mma_word(acc[0], acc[1], a0, a2, w[0].x, w[1].x, w[2].x, w[3].x);
  mma_word(acc[2], acc[3], a0, a2, w[0].y, w[1].y, w[2].y, w[3].y);
  mma_word(acc[4], acc[5], a0, a2, w[0].z, w[1].z, w[2].z, w[3].z);
  mma_word(acc[6], acc[7], a0, a2, w[0].w, w[1].w, w[2].w, w[3].w);
}
__device__ __forceinline__ void blk32(float (&acc)[4][4], uint32_t a0, uint32_t a2, const uint2 (&w)[4]) {
  mma_word(acc[0], acc[1], a0, a2, w[0].x, w[1].x, w[2].x, w[3].x);
  mma_word(acc[2], acc[3], a0, a2, w[0].y, w[1].y, w[2].y, w[3].y);
}
__device__ __forceinline__ void put_act_pair(uint8_t* row, int k, uint32_t v) {
  reinterpret_cast<uint16_t*>(row)[kperm(k)] = (uint16_t)v;
  reinterpret_cast<uint16_t*>(row)[kperm(k + 1)] = (uint16_t)(v >> 16);
}

__device__ __forceinline__ float2 row_stats10(const float (&v)[10], float* s_tmp, int tid) {
  const int warp = tid >> 5, lane = tid & 31;
  float s = 0.f;
#pragma unroll
  for (int i = 0; i < 10; i++) s += v[i];
#pragma unroll
  for (int m = 16; m > 0; m >>= 1) s += __shfl_xor_sync(0xffffffffu, s, m);
  if (lane == 0) s_tmp[warp] = s;
  cbar();
  const float mean = (s_tmp[warp & ~1] + s_tmp[warp | 1]) * (1.0f / kD);
  float q = 0.f;
#pragma unroll
  for (int i = 0; i < 10; i++) { float d = v[i] - mean; q += d * d; }
#pragma unroll
  for (int m = 16; m > 0; m >>= 1) q += __shfl_xor_sync(0xffffffffu, q, m);
  if (lane == 0) s_tmp[8 + warp] = q;
  cbar();
  const float var = bf16r((s_tmp[8 + (warp & ~1)] + s_tmp[8 + (warp | 1)]) * (1.0f / kD));
  return make_float2(bf16r(mean), bf16r(sqrt_fast(bf16r(var + 1e-5f))));
}

__global__ void __launch_bounds__(kThreads, 1)
fused_kernel(const __nv_bfloat16* __restrict__ x, const __nv_bfloat16* __restrict__ kc,
             const __nv_bfloat16* __restrict__ vc, const __nv_bfloat16* __restrict__ wq,
             const __nv_bfloat16* __restrict__ wo, const __nv_bfloat16* __restrict__ wg,
             const __nv_bfloat16* __restrict__ wu, const __nv_bfloat16* __restrict__ wd,
             const __nv_bfloat16* __restrict__ cvec, const __nv_bfloat16* __restrict__ wmod,
             __nv_bfloat16* __restrict__ out) {
  extern __shared__ __align__(1024) uint8_t smem[];
  const uint32_t sbase = (uint32_t)__cvta_generic_to_shared(smem);
  float* s_scores = reinterpret_cast<float*>(smem + kOffScores);
  float* s_x1 = reinterpret_cast<float*>(smem + kOffX1);
  float* s_small = reinterpret_cast<float*>(smem + kOffSmall);
  uint32_t* s_xb2 = reinterpret_cast<uint32_t*>(smem + kOffXb);
  const uint32_t bar_full = sbase + kOffBar;
  const uint32_t bar_empty = sbase + kOffBar + 8 * kNST;
  const uint32_t bar_wo = sbase + kOffBar + 16 * kNST;
  const uint32_t bar_wq = bar_wo + 8;

  const int cta = blockIdx.x;
  const int bb = cta >> 5, hh = cta & 31;
  if (threadIdx.x == 0) {
    for (int s = 0; s < kNST; s++) {
      mbar_init(bar_full + 8 * s, 1);
      mbar_init(bar_empty + 8 * s, kNCW);
    }
    mbar_init(bar_wo, 1);
    mbar_init(bar_wq, 96);
    asm volatile("fence.mbarrier_init.release.cluster;" ::: "memory");
  }
  __syncthreads();

  if (threadIdx.x >= kNCT) {
    asm volatile("setmaxnreg.dec.sync.aligned.u32 40;");
    const int pw = (threadIdx.x - kNCT) >> 5, lane = threadIdx.x & 31;
    if (pw == 0) {
      asm volatile("bar.sync 2, 288;" ::: "memory");
      if (lane == 0) {
        uint64_t pol_stream;
        asm volatile("createpolicy.fractional.L2::evict_first.b64 %0, 1.0;" : "=l"(pol_stream));
        const uint8_t* kp = reinterpret_cast<const uint8_t*>(kc) + (size_t)cta * kSK * kDH * 2;
        const uint8_t* vp = reinterpret_cast<const uint8_t*>(vc) + (size_t)cta * kSK * kDH * 2;
        int st = 0, ph = 0, lst = 0, lph = 0;
#pragma unroll 1
        for (int it = 0; it < kTotTiles; it++) {
          if (st >= kFreeSt) mbar_wait(bar_empty + 8 * st, ph);
          else if (it >= kNST) mbar_wait(bar_empty + 8 * st, ph ^ 1);
#define KDEEP 0
          if (it >= kInflight && it < kTotTiles - KDEEP) {
            mbar_wait(bar_full + 8 * lst, lph);
            if (++lst == kNST) { lst = 0; lph ^= 1; }
          }
          const uint8_t* src = (it < kKTiles) ? kp + (size_t)it * kTileBytes : vp + (size_t)(it - kKTiles) * kTileBytes;
          mbar_expect_tx(bar_full + 8 * st, kTileBytes);
          bulk_load(sbase + kOffRing + st * kTileBytes, src, kTileBytes, bar_full + 8 * st, pol_stream);
          if (++st == kNST) { st = 0; ph ^= 1; }
        }
      }
    } else {
      if (cta < kNQCTA) {
        const int h = threadIdx.x - kNCT - 32;
#pragma unroll 1
        for (int c = h; c < kD * 8; c += 96) {
          const int row = c >> 3, u = c & 7;
          cp_async16(sbase + kOffWq + row * 128 + ((u ^ ((row & 3) << 1)) * 16),
                     wq + (size_t)row * (kH * kDH) + cta * 64 + u * 8);
        }
        asm volatile("cp.async.mbarrier.arrive.noinc.shared.b64 [%0];" ::"r"(bar_wq) : "memory");
      }
      if (pw == 2 && lane < 3) {
        constexpr uint32_t kShare = kD * kF * 2 / kNCTA;
        const __nv_bfloat16* wsel = lane == 0 ? wg : (lane == 1 ? wu : wd);
        asm volatile("cp.async.bulk.prefetch.L2.global [%0], %1;" ::"l"(reinterpret_cast<const uint8_t*>(wsel) + (size_t)cta * kShare),
                     "r"(kShare) : "memory");
      }
      if (pw == 1) {
        asm volatile("bar.sync 3, 288;" ::: "memory");
        asm volatile("fence.proxy.async.shared::cta;" ::: "memory");
        uint64_t pol_norm;
        asm volatile("createpolicy.fractional.L2::evict_normal.b64 %0, 1.0;" : "=l"(pol_norm));
        if (lane == 0) mbar_expect_tx(bar_wo, kWoRows * kD * 2);
        const uint8_t* wp = reinterpret_cast<const uint8_t*>(wo) + (size_t)(hh * kDH + bb * kWoRows) * kD * 2;
#pragma unroll 1
        for (int rr = lane; rr < kWoRows; rr += 32)
          bulk_load(sbase + kOffWo + rr * kWoPitch, wp + rr * (kD * 2), kD * 2, bar_wo, pol_norm);
      }
      asm volatile("cp.async.wait_all;" ::: "memory");
    }
    return;
  }

  asm volatile("setmaxnreg.inc.sync.aligned.u32 232;");
  const int tid = threadIdx.x;
  const int warp = tid >> 5, lane = tid & 31;
  STAMP(0);
  const int mr = lane & 3, mc = lane >> 2;
  const uint32_t act_frag = sbase + kOffAct + (mc & 3) * kActPitch + mr * 4;
  const int rowb = tid >> 6, rowi = tid & 63;
  uint8_t* arow = smem + kOffAct + rowb * kActPitch;

  uint32_t c2[5], x2[5];
#pragma unroll
  for (int i = 0; i < 5; i++) {
    c2[i] = reinterpret_cast<const uint32_t*>(cvec)[rowb * (kD / 2) + rowi + 64 * i];
    x2[i] = reinterpret_cast<const uint32_t*>(x)[rowb * (kD / 2) + rowi + 64 * i];
  }
  const uint32_t tag = *reinterpret_cast<volatile unsigned*>(&g_epoch) + 1u;
  if (cta == kNCTA - 1) {
#pragma unroll 1
    for (int i = tid; i < kB * kD; i += kNCT) g_y[(tag + 1) & 1][i] = 0.f;
  }
  if (cta < kNModCTA) {
    const int row = tid >> 2, u = tid & 3;
    const __nv_bfloat16* src = wmod + (size_t)row * (6 * kD) + cta * 32 + u * 8;
    uint32_t dst = sbase + kOffWmod + row * 64 + ((u ^ (((row >> 1) & 1) << 1)) * 16);
#pragma unroll 1
    for (int i = 0; i < 10; i++) { cp_async16(dst, src); dst += 64 * 64; src += (size_t)64 * (6 * kD); }
  }
  asm volatile("cp.async.commit_group;" ::: "memory");
  float xv[10];
#pragma unroll
  for (int i = 0; i < 5; i++) {
    const float c0 = bflo(c2[i]), c1 = bfhi(c2[i]);
    put_act_pair(arow, 2 * (rowi + 64 * i),
                 pack_bf16(__fdividef(c0, 1.0f + __expf(-c0)), __fdividef(c1, 1.0f + __expf(-c1))));
    s_xb2[rowb * (kD / 2) + rowi + 64 * i] = x2[i];
    xv[2 * i] = bflo(x2[i]);
    xv[2 * i + 1] = bfhi(x2[i]);
  }
  {
    const float2 st2 = row_stats10(xv, s_small, tid);
#pragma unroll
    for (int i = 0; i < 10; i++) xv[i] = bf16r(__fdividef(bf16r(xv[i] - st2.x), st2.y));
  }
  asm volatile("bar.arrive 2, 288;" ::: "memory");
  asm volatile("cp.async.wait_group 0;" ::: "memory");
  cbar();
  if (cta < kNModCTA) {
    float acc[4][4];
#pragma unroll
    for (int i = 0; i < 4; i++)
#pragma unroll
      for (int k = 0; k < 4; k++) acc[i][k] = 0.f;
#pragma unroll 1
    for (int ks = 0; ks < 5; ks++) {
      const int kb = (warp * 5 + ks) * 16;
      uint2 w[4];
#pragma unroll
      for (int t = 0; t < 4; t++) {
        const int row = kb + 4 * t + mr;
        w[t] = lds64(sbase + kOffWmod + row * 64 + ((mc ^ (((row >> 1) & 1) << 2)) * 8));
      }
      blk32(acc, lds32(act_frag + kb * 2), lds32(act_frag + kb * 2 + 16), w);
    }
    if (mc < 4) {
      float4* red = reinterpret_cast<float4*>(s_scores + warp * 128 + mc * 32 + mr * 8);
      red[0] = make_float4(acc[0][0], acc[1][0], acc[2][0], acc[3][0]);
      red[1] = make_float4(acc[0][1], acc[1][1], acc[2][1], acc[3][1]);
    }
  }
  cbar();
  if (cta < kNModCTA && tid < 64) {
    float2 s = make_float2(0.f, 0.f);
#pragma unroll
    for (int w = 0; w < kNCW; w++) {
      const float2 v = *reinterpret_cast<const float2*>(s_scores + w * 128 + tid * 2);
      s.x += v.x; s.y += v.y;
    }
    put_tagged(&g_modt[(tid >> 4) * (3 * kD) + cta * 16 + (tid & 15)], tag, pack_bf16(s.x, s.y));
  }
  STAMP(1);

  if (cta < kNQCTA) {
    {
      uint32_t sa[5], ca[5];
      get_tagged<5>(sa, &g_modt[rowb * (3 * kD) + rowi], 64, tag);
      get_tagged<5>(ca, &g_modt[rowb * (3 * kD) + kD / 2 + rowi], 64, tag);
#pragma unroll
      for (int i = 0; i < 5; i++)
        put_act_pair(arow, 2 * (rowi + 64 * i),
                     pack_bf16(bf16r(xv[2 * i] * bf16r(1.0f + bflo(ca[i]))) + bflo(sa[i]),
                               bf16r(xv[2 * i + 1] * bf16r(1.0f + bfhi(ca[i]))) + bfhi(sa[i])));
    }
    cbar();
    float acc[8][4];
#pragma unroll
    for (int i = 0; i < 8; i++)
#pragma unroll
      for (int k = 0; k < 4; k++) acc[i][k] = 0.f;
    mbar_wait(bar_wq, 0);
#pragma unroll 1
    for (int ks = 0; ks < 5; ks++) {
      const int kb = (warp * 5 + ks) * 16;
      uint4 w[4];
#pragma unroll
      for (int t = 0; t < 4; t++) w[t] = lds128(sbase + kOffWq + (kb + 4 * t + mr) * 128 + ((mc ^ (mr << 1)) * 16));
      blk64(acc, lds32(act_frag + kb * 2), lds32(act_frag + kb * 2 + 16), w);
    }
    if (mc < 4) {
      float4* red = reinterpret_cast<float4*>(s_scores + warp * 256 + mc * 64 + mr * 16);
      red[0] = make_float4(acc[0][0], acc[1][0], acc[2][0], acc[3][0]);
      red[1] = make_float4(acc[4][0], acc[5][0], acc[6][0], acc[7][0]);
      red[2] = make_float4(acc[0][1], acc[1][1], acc[2][1], acc[3][1]);
      red[3] = make_float4(acc[4][1], acc[5][1], acc[6][1], acc[7][1]);
    }
    cbar();
    if (tid < 128) {
      float2 s = make_float2(0.f, 0.f);
#pragma unroll
      for (int w = 0; w < kNCW; w++) {
        const float2 v = *reinterpret_cast<const float2*>(s_scores + w * 256 + tid * 2);
        s.x += v.x; s.y += v.y;
      }
      put_tagged(&g_qt[(tid >> 5) * (kH * kDH / 2) + cta * 32 + (tid & 31)], tag, pack_bf16(s.x, s.y));
    }
  }
  asm volatile("fence.proxy.async.shared::cta;" ::: "memory");
  __syncwarp();
  if (lane == 0) {
#pragma unroll
    for (int s = kFreeSt; s < kNST; s++) mbar_arrive(bar_empty + 8 * s);
  }
  asm volatile("bar.arrive 3, 288;" ::: "memory");
  STAMP(2);

  const int j = lane & 7, g = lane >> 3;
  {
    constexpr bool real = true;
    float oa[24];
    uint2 wgu[5][4];
    uint32_t wdn[12][4];
    uint32_t gav[5], sbv[5], cbv[5], gbv[1];
#pragma unroll
    for (int i = 0; i < 24; i++) oa[i] = 0.f;
    if (real) {
      if (tid < kDH / 2) {
        uint32_t qv[1];
        get_tagged<1>(qv, &g_qt[bb * (kH * kDH / 2) + hh * (kDH / 2) + tid], 0, tag);
        *reinterpret_cast<float2*>(s_small + 32 + 2 * tid) = make_float2(bflo(qv[0]), bfhi(qv[0]));
      }
      cbar();
      STAMP(3);
      float qf[24];
#pragma unroll
      for (int i = 0; i < 3; i++)
#pragma unroll
        for (int e = 0; e < 8; e += 4) {
          const float4 v = *reinterpret_cast<const float4*>(s_small + 32 + (j + 8 * i) * 8 + e);
          qf[i * 8 + e] = v.x; qf[i * 8 + e + 1] = v.y; qf[i * 8 + e + 2] = v.z; qf[i * 8 + e + 3] = v.w;
        }

      const float scale = 0.07216878364870322f;
      float lmax = -INFINITY;
      int it = 0, st = 0, ph = 0;
      auto k_tiles = [&](int end) {
#pragma unroll 1
      for (; it < end; it++) {
        mbar_wait(bar_full + 8 * st, ph);
        const uint32_t base = sbase + kOffRing + st * kTileBytes + (warp * 8 + g) * (kDH * 2) + j * 16;
        uint4 kv[2][3];
#pragma unroll
        for (int u = 0; u < 2; u++)
#pragma unroll
          for (int i = 0; i < 3; i++) kv[u][i] = lds128(base + u * 4 * (kDH * 2) + i * 128);
        float sc[2];
#pragma unroll
        for (int u = 0; u < 2; u++) {
          float a0 = 0.f, a1 = 0.f;
#pragma unroll
          for (int i = 0; i < 3; i++) {
            a0 += qf[i * 8 + 0] * bflo(kv[u][i].x); a1 += qf[i * 8 + 1] * bfhi(kv[u][i].x);
            a0 += qf[i * 8 + 2] * bflo(kv[u][i].y); a1 += qf[i * 8 + 3] * bfhi(kv[u][i].y);
            a0 += qf[i * 8 + 4] * bflo(kv[u][i].z); a1 += qf[i * 8 + 5] * bfhi(kv[u][i].z);
            a0 += qf[i * 8 + 6] * bflo(kv[u][i].w); a1 += qf[i * 8 + 7] * bfhi(kv[u][i].w);
          }
          sc[u] = a0 + a1;
        }
        __syncwarp();
        if (lane == 0) mbar_arrive(bar_empty + 8 * st);
        if (++st == kNST) { st = 0; ph ^= 1; }
#pragma unroll
        for (int m = 1; m < 8; m <<= 1) {
          sc[0] += __shfl_xor_sync(0xffffffffu, sc[0], m);
          sc[1] += __shfl_xor_sync(0xffffffffu, sc[1], m);
        }
#pragma unroll
        for (int u = 0; u < 2; u++) {
          const float s = bf16r(bf16r(sc[u]) * scale);
          lmax = fmaxf(lmax, s);
          if (j == 0) s_scores[it * kTileKeys + warp * 8 + u * 4 + g] = s;
        }
      }
      };
      const __nv_bfloat16* wsrc_gu = (mc < 4 ? wg : wu) + (size_t)(warp * 80 + mr) * kF + cta * 16 + (mc & 3) * 4;
      const __nv_bfloat16* wsrc_d = wd + (size_t)(warp * 192 + mr) * kD + cta * 16 + mc * 2;
      k_tiles(4);
      if (cta < kNFCTA) {
        const unsigned long long* pm = &g_modt[rowb * (3 * kD) + 2 * (kD / 2) + rowi];
        const unsigned long long* pg = &g_modt[((tid >> 3) & 3) * (3 * kD) + 5 * (kD / 2) + (cta % kNDCTA) * 8 + (tid & 7)];
        int spin = 0;
        bool ok;
        do {
          ok = true;
#pragma unroll
          for (int i = 0; i < 5; i++) {
            const unsigned long long v0 = ld_relaxed64(pm + i * 64), v1 = ld_relaxed64(pm + kD / 2 + i * 64),
                                     v2 = ld_relaxed64(pm + kD + i * 64);
            gav[i] = (uint32_t)v0; sbv[i] = (uint32_t)v1; cbv[i] = (uint32_t)v2;
            ok = ok && ((uint32_t)(v0 >> 32) == tag) && ((uint32_t)(v1 >> 32) == tag) && ((uint32_t)(v2 >> 32) == tag);
          }
          const unsigned long long v3 = ld_relaxed64(pg);
          gbv[0] = (uint32_t)v3;
          ok = ok && ((uint32_t)(v3 >> 32) == tag);
        } while (!ok && ++spin < (1 << 22));
      }
      k_tiles(8);
      if (cta < kNFCTA) {
#pragma unroll
        for (int i = 0; i < 10; i++) wgu[i >> 2][i & 3] = ldg64(wsrc_gu + (size_t)(i * 4) * kF);
      }
      k_tiles(16);
      if (cta < kNFCTA) {
#pragma unroll
        for (int i = 10; i < 20; i++) wgu[i >> 2][i & 3] = ldg64(wsrc_gu + (size_t)(i * 4) * kF);
      }
      k_tiles(24);
      if (cta < kNDCTA) {
#pragma unroll
        for (int i = 0; i < 12; i++) wdn[i >> 2][i & 3] = ldg32(wsrc_d + (size_t)(i * 4) * kD);
      }
      k_tiles(32);
      if (cta < kNDCTA) {
#pragma unroll
        for (int i = 12; i < 24; i++) wdn[i >> 2][i & 3] = ldg32(wsrc_d + (size_t)(i * 4) * kD);
      }
      k_tiles(40);
      if (cta < kNDCTA) {
#pragma unroll
        for (int i = 24; i < 36; i++) wdn[i >> 2][i & 3] = ldg32(wsrc_d + (size_t)(i * 4) * kD);
      }
      k_tiles(48);
      if (cta < kNDCTA) {
#pragma unroll
        for (int i = 36; i < 48; i++) wdn[i >> 2][i & 3] = ldg32(wsrc_d + (size_t)(i * 4) * kD);
      }
      k_tiles(kKTiles);
      STAMP(4);
#pragma unroll
      for (int m = 16; m > 0; m >>= 1) lmax = fmaxf(lmax, __shfl_xor_sync(0xffffffffu, lmax, m));
      if (lane == 0) s_small[warp] = lmax;
      cbar();
      {
        float gmax = s_small[0];
#pragma unroll
        for (int w = 1; w < kNCW; w++) gmax = fmaxf(gmax, s_small[w]);
        float ev[16];
        float lsum = 0.f;
#pragma unroll
        for (int i = 0; i < 16; i++) {
          ev[i] = __expf(s_scores[tid + kNCT * i] - gmax);
          lsum += ev[i];
        }
#pragma unroll
        for (int m = 16; m > 0; m >>= 1) lsum += __shfl_xor_sync(0xffffffffu, lsum, m);
        if (lane == 0) s_small[8 + warp] = lsum;
        cbar();
        float gsum = 0.f;
#pragma unroll
        for (int w = 0; w < kNCW; w++) gsum += s_small[8 + w];
        const float inv = __fdividef(1.0f, gsum);
#pragma unroll
        for (int i = 0; i < 16; i++) s_scores[tid + kNCT * i] = bf16r(ev[i] * inv);
      }
      cbar();
      STAMP(5);
#pragma unroll 1
      for (; it < kTotTiles; it++) {
        mbar_wait(bar_full + 8 * st, ph);
        const uint32_t base = sbase + kOffRing + st * kTileBytes + (warp * 8 + g) * (kDH * 2) + j * 16;
        uint4 vv[2][3];
#pragma unroll
        for (int u = 0; u < 2; u++)
#pragma unroll
          for (int i = 0; i < 3; i++) vv[u][i] = lds128(base + u * 4 * (kDH * 2) + i * 128);
        float p[2];
#pragma unroll
        for (int u = 0; u < 2; u++) p[u] = s_scores[(it - kKTiles) * kTileKeys + warp * 8 + u * 4 + g];
#pragma unroll
        for (int u = 0; u < 2; u++)
#pragma unroll
          for (int i = 0; i < 3; i++) fma8(oa + 8 * i, vv[u][i], p[u]);
        __syncwarp();
        if (lane == 0) mbar_arrive(bar_empty + 8 * st);
        if (++st == kNST) { st = 0; ph ^= 1; }
      }
    }

#pragma unroll
    for (int i = 0; i < 24; i++) {
      oa[i] += __shfl_xor_sync(0xffffffffu, oa[i], 8);
      oa[i] += __shfl_xor_sync(0xffffffffu, oa[i], 16);
    }
    cbar();
    STAMP(6);
    if (g == 0) {
#pragma unroll
      for (int i = 0; i < 3; i++) {
        float4* dst = reinterpret_cast<float4*>(s_scores + warp * kDH + (j + 8 * i) * 8);
        dst[0] = make_float4(oa[i * 8], oa[i * 8 + 1], oa[i * 8 + 2], oa[i * 8 + 3]);
        dst[1] = make_float4(oa[i * 8 + 4], oa[i * 8 + 5], oa[i * 8 + 6], oa[i * 8 + 7]);
      }
    }
    cbar();
    if (tid < kDH / 2) {
      float2 s = make_float2(0.f, 0.f);
#pragma unroll
      for (int w = 0; w < kNCW; w++) {
        const float2 v = *reinterpret_cast<const float2*>(s_scores + w * kDH + tid * 2);
        s.x += v.x; s.y += v.y;
      }
      if (real) put_tagged(&g_ot[(hh * kB + bb) * (kDH / 2) + tid], tag, pack_bf16(s.x, s.y));
    }
    if (tid < 96) {
      const int b = tid / 24, w = tid - b * 24;
      uint32_t ov[1];
      get_tagged<1>(ov, &g_ot[(hh * kB + b) * (kDH / 2) + bb * 24 + w], 0, tag, real);
      put_act_pair(smem + kOffAct + b * kActPitch, 2 * w, ov[0]);
    }
    if (real) mbar_wait(bar_wo, 0);
    cbar();
    STAMP(7);

    {
      float acc[8][4];
#pragma unroll 1
      for (int blk = warp; blk < 10; blk += 8) {
#pragma unroll
        for (int k = 0; k < 8; k++)
#pragma unroll
          for (int e = 0; e < 4; e++) acc[k][e] = 0.f;
#pragma unroll
        for (int ws = 0; ws < 3; ws++) {
          const uint32_t base = sbase + kOffWo + (ws * 16 + mr) * kWoPitch + blk * 128 + mc * 16;
          uint4 w[4];
#pragma unroll
          for (int t = 0; t < 4; t++) w[t] = lds128(base + t * 4 * kWoPitch);
          blk64(acc, lds32(act_frag + ws * 32), lds32(act_frag + ws * 32 + 16), w);
        }
        if (mc < 4 && real) {
          float* dst = &g_y[tag & 1][mc * kD + blk * 64 + mr * 16];
          red_add_v4(dst + 0, acc[0][0], acc[1][0], acc[2][0], acc[3][0]);
          red_add_v4(dst + 4, acc[4][0], acc[5][0], acc[6][0], acc[7][0]);
          red_add_v4(dst + 8, acc[0][1], acc[1][1], acc[2][1], acc[3][1]);
          red_add_v4(dst + 12, acc[4][1], acc[5][1], acc[6][1], acc[7][1]);
        }
      }
    }
    cbar();
    if (tid == 0 && real) signal_cnt(kCntY);
    STAMP(8);
    if (cta >= kNFCTA) return;

    if (tid == 0) {
      wait_cnt(kCntY, tag * kNCTA);
      if (cta == 0) g_epoch = tag;
    }
    cbar();
    STAMP(9);
    {
      float x1[10];
#pragma unroll
      for (int i = 0; i < 5; i++) {
        const int u = rowi + 64 * i;
        const float2 y = __ldcg(reinterpret_cast<const float2*>(g_y[tag & 1]) + rowb * (kD / 2) + u);
        const uint32_t xx = s_xb2[rowb * (kD / 2) + u];
        x1[2 * i] = bf16r(bflo(xx) + bf16r(bflo(gav[i]) * bf16r(y.x)));
        x1[2 * i + 1] = bf16r(bfhi(xx) + bf16r(bfhi(gav[i]) * bf16r(y.y)));
      }
      const float2 st2 = row_stats10(x1, s_small, tid);
#pragma unroll
      for (int i = 0; i < 5; i++) {
        const int u = rowi + 64 * i;
        const float h0 = bf16r(__fdividef(bf16r(x1[2 * i] - st2.x), st2.y));
        const float h1 = bf16r(__fdividef(bf16r(x1[2 * i + 1] - st2.x), st2.y));
        *reinterpret_cast<float2*>(s_x1 + rowb * kD + 2 * u) = make_float2(x1[2 * i], x1[2 * i + 1]);
        put_act_pair(arow, 2 * u,
                     pack_bf16(bf16r(h0 * bf16r(1.0f + bflo(cbv[i]))) + bflo(sbv[i]),
                               bf16r(h1 * bf16r(1.0f + bfhi(cbv[i]))) + bfhi(sbv[i])));
      }
    }
    cbar();
    STAMP(13);
    {
      float acc[4][4];
#pragma unroll
      for (int i = 0; i < 4; i++)
#pragma unroll
        for (int k = 0; k < 4; k++) acc[i][k] = 0.f;
#pragma unroll
      for (int ks = 0; ks < 5; ks++) {
        const int kb = (warp * 5 + ks) * 16;
        blk32(acc, lds32(act_frag + kb * 2), lds32(act_frag + kb * 2 + 16), wgu[ks]);
      }
      if (mc < 4) {
        float4* red = reinterpret_cast<float4*>(s_scores + warp * 128 + mc * 32 + mr * 8);
        red[0] = make_float4(acc[0][0], acc[1][0], acc[2][0], acc[3][0]);
        red[1] = make_float4(acc[0][1], acc[1][1], acc[2][1], acc[3][1]);
      }
    }
    cbar();
    STAMP(14);
    if (tid < 32) {
      const int b = tid >> 3, cp = tid & 7;
      float2 gs = make_float2(0.f, 0.f), us = make_float2(0.f, 0.f);
#pragma unroll
      for (int w = 0; w < kNCW; w++) {
        const float2 gv = *reinterpret_cast<const float2*>(s_scores + w * 128 + b * 32 + 2 * cp);
        const float2 uv = *reinterpret_cast<const float2*>(s_scores + w * 128 + b * 32 + 16 + 2 * cp);
        gs.x += gv.x; gs.y += gv.y; us.x += uv.x; us.y += uv.y;
      }
      const uint32_t av = pack_bf16(bf16r(gelu_tanh(bf16r(gs.x))) * bf16r(us.x), bf16r(gelu_tanh(bf16r(gs.y))) * bf16r(us.y));
      if (real) put_tagged(&g_actt[b * (kF / 2) + cta * 8 + cp], tag, av);
    }
    STAMP(10);
    if (cta >= kNDCTA) return;

    {
      uint32_t av[12];
      get_tagged<12>(av, &g_actt[tid], kNCT, tag, real);
      cbar();
#pragma unroll
      for (int i = 0; i < 12; i++) {
        const int wd_i = tid + kNCT * i;
        const int b = wd_i / (kF / 2), w = wd_i - b * (kF / 2);
        put_act_pair(smem + kOffAct + b * kActPitch, 2 * w, av[i]);
      }
      cbar();
      STAMP(11);
      float acc[2][4];
#pragma unroll
      for (int i = 0; i < 2; i++)
#pragma unroll
        for (int k = 0; k < 4; k++) acc[i][k] = 0.f;
#pragma unroll
      for (int ks = 0; ks < 12; ks++) {
        const int kb = (warp * 12 + ks) * 16;
        mma_word(acc[0], acc[1], lds32(act_frag + kb * 2), lds32(act_frag + kb * 2 + 16), wdn[ks][0], wdn[ks][1],
                 wdn[ks][2], wdn[ks][3]);
      }
      if (mc < 4) {
        float4* red = reinterpret_cast<float4*>(s_scores + warp * 64 + mc * 16 + mr * 4);
        red[0] = make_float4(acc[0][0], acc[1][0], acc[0][1], acc[1][1]);
      }
      cbar();
      if (tid < 32) {
        float2 s = make_float2(0.f, 0.f);
#pragma unroll
        for (int w = 0; w < kNCW; w++) {
          const float2 v = *reinterpret_cast<const float2*>(s_scores + w * 64 + tid * 2);
          s.x += v.x; s.y += v.y;
        }
        const int b = tid >> 3, d = cta * 16 + (tid & 7) * 2;
        const float2 x1 = *reinterpret_cast<const float2*>(s_x1 + b * kD + d);
        const uint32_t ov = pack_bf16(x1.x + bf16r(bflo(gbv[0]) * bf16r(s.x)), x1.y + bf16r(bfhi(gbv[0]) * bf16r(s.y)));
        if (real) reinterpret_cast<uint32_t*>(out)[(b * kD + d) / 2] = ov;
      }
    }
    STAMP(12);
  }
}

}

extern "C" void kernel_launch(void* const* d_in, const int* in_sizes, int n_in, void* d_out, int out_size) {
  const __nv_bfloat16* x = (const __nv_bfloat16*)d_in[0];
  const __nv_bfloat16* kc = (const __nv_bfloat16*)d_in[1];
  const __nv_bfloat16* vc = (const __nv_bfloat16*)d_in[2];
  const __nv_bfloat16* wq = (const __nv_bfloat16*)d_in[3];
  const __nv_bfloat16* wo = (const __nv_bfloat16*)d_in[4];
  const __nv_bfloat16* wg = (const __nv_bfloat16*)d_in[6];
  const __nv_bfloat16* wu = (const __nv_bfloat16*)d_in[7];
  const __nv_bfloat16* wd = (const __nv_bfloat16*)d_in[8];
  const __nv_bfloat16* cv = (const __nv_bfloat16*)d_in[9];
  const __nv_bfloat16* wmod = (const __nv_bfloat16*)d_in[10];
  static bool attr_done = false;
  if (!attr_done) {
    cudaFuncSetAttribute(fused_kernel, cudaFuncAttributeMaxDynamicSharedMemorySize, kSmemBytes);
    attr_done = true;
  }
  fused_kernel<<<kNCTA, kThreads, kSmemBytes>>>(x, kc, vc, wq, wo, wg, wu, wd, cv, wmod, (__nv_bfloat16*)d_out);
}
```

```cpp
#include <cuda.h>
#include <cuda_runtime.h>
#include <cuda_bf16.h>
#include <stdint.h>

namespace {

constexpr int kB = 4, kD = 640, kH = 32, kSK = 4096, kDH = 192, kF = 1536;
constexpr int kNCTA = 128;
constexpr int kTileKeys = 64;
constexpr int kTileBytes = kTileKeys * kDH * 2;
constexpr int kNST = 5;
constexpr int kInflight = 3;
constexpr int kNCW = 8;
constexpr int kNCT = kNCW * 32;
constexpr int kThreads = kNCT + 128;
constexpr int kKTiles = kSK / kTileKeys;
constexpr int kTotTiles = 2 * kKTiles;
constexpr int kNWCTA = 120;
constexpr int kWoK = kH * kDH / 3;
constexpr int kNModCTA = 120;
constexpr int kNQCTA = 96;
constexpr int kNFCTA = 96;
constexpr int kNDCTA = 40;

constexpr int kOffRing = 0;
constexpr int kOffWo = kNST * kTileBytes;
constexpr int kFreeSt = 2;
constexpr int kOffWq = kFreeSt * kTileBytes;
constexpr int kOffWmod = kOffWq + kD * 128;
constexpr int kOffWg = kOffWo;
constexpr int kOffWu = kOffWg + kD * 32;
constexpr int kOffWd = 0;
constexpr int kS = 32;
constexpr int kFirstClaim = kTotTiles - kS;
constexpr uint32_t kDescSteal = 0x8000u, kDescEnd = 0xffffu;
constexpr int kChunk = 2;
constexpr int kMinR = 3;
constexpr int kMaxTake = 2;
constexpr int kOffScores = kOffWo + kWoK * 32;
constexpr int kOffAct = kOffScores + kSK * 4;
constexpr int kActPitch = kF * 2 + 16;
constexpr int kOffSmall = kOffAct + kB * kActPitch;
constexpr int kOffXb = kOffSmall + 1024;
constexpr int kOffX1 = kOffXb + kB * kD * 2;
constexpr int kOffPst = kOffX1 + kB * 16 * 4;
constexpr int kOffBar = kOffPst + kNST * 128;
constexpr int kSmemBytes = kOffBar + 256;
static_assert(kSmemBytes <= 232448, "smem");
static_assert(kOffWmod + kD * 64 <= kOffScores, "prologue weights");
static_assert(kOffWo % 128 == 0 && kOffScores % 16 == 0 && kOffAct % 16 == 0, "align");

#define STAMP(k)

__device__ unsigned long long g_modt[kB * 6 * kD / 2];
__device__ unsigned long long g_qt[kB * kH * kDH / 2];
__device__ __align__(16) unsigned long long g_ot[kB * kH * kDH / 2];
__device__ __align__(16) uint32_t g_yt[3 * kB * kD];
__device__ unsigned g_cnt[64];
__device__ unsigned g_epoch;
__device__ unsigned g_prog[32];
__device__ __align__(16) uint32_t g_claim[kNCTA];
__device__ __align__(16) __nv_bfloat16 g_p[kNCTA * kS * kTileKeys];
#define g_actt reinterpret_cast<unsigned long long*>(g_p)
__device__ __align__(16) unsigned long long g_part[kNCTA * kS * kDH];

constexpr int kCntV = 0, kCntY = 1;
#define PACET 256
constexpr int kPaceT = PACET, kPaceStart = 8;
__device__ __forceinline__ int cl_front(uint32_t w) { return (int)(w & 0xffu); }
__device__ __forceinline__ int cl_stolen(uint32_t w) { return (int)((w >> 8) & 0xfffu); }

__device__ __forceinline__ uint32_t scan_claims(uint32_t ptag, int cta, int lane) {
  uint32_t w[4];
  asm volatile("ld.relaxed.gpu.global.v4.u32 {%0, %1, %2, %3}, [%4];" : "=r"(w[0]), "=r"(w[1]), "=r"(w[2]), "=r"(w[3]) : "l"(&g_claim[lane * 4]) : "memory");
  uint32_t best = 0;
#pragma unroll
  for (int i = 0; i < 4; i++) {
    const int r = kS - cl_front(w[i]) - cl_stolen(w[i]);
    const uint32_t v = lane * 4 + i;
    if (((w[i] ^ (ptag << 20)) >> 20) == 0 && r > 0) best = max(best, ((uint32_t)r << 16) | (((v * 37u + cta * 59u) & 127u) << 8) | v);
  }
  return __reduce_max_sync(0xffffffffu, best);
}
__device__ __forceinline__ uint32_t wait_dec(volatile uint32_t* p) {
  uint32_t v;
  int it = 0;
  do { v = *p; } while (v == 0 && ++it < (1 << 22));
  return v;
}

__device__ __forceinline__ float bf16r(float x) { return __bfloat162float(__float2bfloat16_rn(x)); }
__device__ __forceinline__ float bflo(uint32_t u) { return __uint_as_float(u << 16); }
__device__ __forceinline__ float bfhi(uint32_t u) { return __uint_as_float(u & 0xffff0000u); }
__device__ __forceinline__ uint32_t pack_bf16(float lo, float hi) {
  __nv_bfloat162 v = __floats2bfloat162_rn(lo, hi);
  return *reinterpret_cast<uint32_t*>(&v);
}

__device__ __forceinline__ void mbar_init(uint32_t bar, uint32_t count) {
  asm volatile("mbarrier.init.shared::cta.b64 [%0], %1;" ::"r"(bar), "r"(count) : "memory");
}
__device__ __forceinline__ void mbar_expect_tx(uint32_t bar, uint32_t bytes) {
  asm volatile("mbarrier.arrive.expect_tx.shared::cta.b64 _, [%0], %1;" ::"r"(bar), "r"(bytes) : "memory");
}
__device__ __forceinline__ void mbar_arrive(uint32_t bar) {
  asm volatile("mbarrier.arrive.shared::cta.b64 _, [%0];" ::"r"(bar) : "memory");
}
__device__ __forceinline__ void mbar_wait(uint32_t bar, uint32_t parity) {
  uint32_t ok;
  int it = 0;
  do {
    asm volatile(
        "{ .reg .pred p; mbarrier.try_wait.parity.shared::cta.b64 p, [%1], %2; selp.u32 %0, 1, 0, p; }"
        : "=r"(ok)
        : "r"(bar), "r"(parity)
        : "memory");
    if (++it > (1 << 22)) break;
  } while (!ok);
}
__device__ __forceinline__ void bulk_load(uint32_t dst, const void* src, uint32_t bytes, uint32_t bar,
                                          uint64_t policy) {
  asm volatile(
      "cp.async.bulk.shared::cluster.global.mbarrier::complete_tx::bytes.L2::cache_hint [%0], [%1], %2, [%3], %4;" ::"r"(dst),
      "l"(src), "r"(bytes), "r"(bar), "l"(policy)
      : "memory");
}
__device__ __forceinline__ void tma_load_2d(uint32_t dst, const CUtensorMap* tm, int c0, int c1, uint32_t bar) {
  asm volatile(
      "cp.async.bulk.tensor.2d.shared::cluster.global.mbarrier::complete_tx::bytes [%0], [%1, {%2, %3}], [%4];" ::"r"(dst),
      "l"(reinterpret_cast<uint64_t>(tm)), "r"(c0), "r"(c1), "r"(bar)
      : "memory");
}
template <int GRP, int PACE>
__device__ __forceinline__ void slice_load(uint32_t dst, const __nv_bfloat16* src, int pitch, int rows, uint32_t bar, int lane) {
  const int r0 = lane >> 1, ch = lane & 1;
  const __nv_bfloat16* sp = src + (size_t)r0 * pitch + ch * 8;
  const uint32_t dp = dst + r0 * 32 + ((ch ^ ((r0 >> 2) & 1)) << 4);
#pragma unroll 1
  for (int r = 0; r < rows; r += 16 * GRP) {
    if (PACE && r) __nanosleep(PACE);
#pragma unroll
    for (int i = 0; i < GRP; i++)
      asm volatile("cp.async.cg.shared.global.L2::128B [%0], [%1], 16;" ::"r"(dp + (r + 16 * i) * 32), "l"(sp + (size_t)(r + 16 * i) * pitch) : "memory");
  }
  asm volatile("cp.async.mbarrier.arrive.noinc.shared::cta.b64 [%0];" ::"r"(bar) : "memory");
}
__device__ __forceinline__ void cbar() { asm volatile("bar.sync 1, 256;" ::: "memory"); }

__device__ __forceinline__ unsigned ld_relaxed32(const unsigned* p) {
  unsigned v;
  asm volatile("ld.relaxed.gpu.global.u32 %0, [%1];" : "=r"(v) : "l"(p) : "memory");
  return v;
}
__device__ __forceinline__ void wait_cnt(int idx, unsigned target) {
  const unsigned* p = &g_cnt[idx * 32];
  int it = 0;
  while ((int)(ld_relaxed32(p) - target) < 0) {
    if (++it > (1 << 24)) break;
  }
}
__device__ __forceinline__ void hint_cnt(int idx) {
  asm volatile("red.relaxed.gpu.global.add.u32 [%0], 1;" ::"l"(&g_cnt[idx * 32]) : "memory");
}
__device__ __forceinline__ void put_tagged(unsigned long long* p, uint32_t tag, uint32_t payload) {
  const unsigned long long v = ((unsigned long long)tag << 32) | payload;
  asm volatile("st.relaxed.gpu.global.u64 [%0], %1;" ::"l"(p), "l"(v) : "memory");
}
__device__ __forceinline__ unsigned long long ld_relaxed64(const unsigned long long* p) {
  unsigned long long v;
  asm volatile("ld.relaxed.gpu.global.u64 %0, [%1];" : "=l"(v) : "l"(p) : "memory");
  return v;
}
template <int N>
__device__ __forceinline__ void get_tagged(uint32_t (&val)[N], const unsigned long long* p, int stride, uint32_t tag) {
  int it = 0;
  bool ok;
  do {
    ok = true;
#pragma unroll
    for (int i = 0; i < N; i++) {
      const unsigned long long v = ld_relaxed64(p + i * stride);
      val[i] = (uint32_t)v;
      ok = ok && ((uint32_t)(v >> 32) == tag);
    }
    if (++it > (1 << 22)) break;
  } while (!ok);
}

__device__ __forceinline__ uint4 lds128(uint32_t addr) {
  uint4 v;
  asm volatile("ld.shared.v4.u32 {%0, %1, %2, %3}, [%4];" : "=r"(v.x), "=r"(v.y), "=r"(v.z), "=r"(v.w) : "r"(addr));
  return v;
}
__device__ __forceinline__ uint2 lds64(uint32_t addr) {
  uint2 v;
  asm volatile("ld.shared.v2.u32 {%0, %1}, [%2];" : "=r"(v.x), "=r"(v.y) : "r"(addr));
  return v;
}
__device__ __forceinline__ uint32_t lds32(uint32_t addr) {
  uint32_t v;
  asm volatile("ld.shared.u32 %0, [%1];" : "=r"(v) : "r"(addr));
  return v;
}
__device__ __forceinline__ void fma8(float* acc, uint4 w, float s) {
  acc[0] += s * bflo(w.x); acc[1] += s * bfhi(w.x);
  acc[2] += s * bflo(w.y); acc[3] += s * bfhi(w.y);
  acc[4] += s * bflo(w.z); acc[5] += s * bfhi(w.z);
  acc[6] += s * bflo(w.w); acc[7] += s * bfhi(w.w);
}

__device__ __forceinline__ float gelu_tanh(float x) {
  const float k0 = 0.7978845608028654f, k1 = 0.044715f;
  float inner = k0 * (x + k1 * x * x * x);
  float th = 1.0f - __fdividef(2.0f, 1.0f + __expf(2.0f * inner));
  return 0.5f * x * (1.0f + th);
}
__device__ __forceinline__ float sqrt_fast(float x) {
  float r;
  asm("sqrt.approx.f32 %0, %1;" : "=f"(r) : "f"(x));
  return r;
}

__device__ __forceinline__ void mma16816(float (&c)[4], uint32_t a0, uint32_t a2, uint32_t b0, uint32_t b1) {
  asm volatile(
      "mma.sync.aligned.m16n8k16.row.col.f32.bf16.bf16.f32 {%0,%1,%2,%3}, {%4,%5,%6,%7}, {%8,%9}, {%0,%1,%2,%3};"
      : "+f"(c[0]), "+f"(c[1]), "+f"(c[2]), "+f"(c[3])
      : "r"(a0), "r"(0u), "r"(a2), "r"(0u), "r"(b0), "r"(b1));
}
__device__ __forceinline__ int kperm(int k) {
  return (k & ~15) | (((k >> 3) & 1) << 3) | ((k & 3) << 1) | ((k >> 2) & 1);
}
__device__ __forceinline__ void mma_word(float (&lo)[4], float (&hi)[4], uint32_t a0, uint32_t a2, uint32_t w0,
                                         uint32_t w1, uint32_t w2, uint32_t w3) {
  mma16816(lo, a0, a2, __byte_perm(w0, w1, 0x5410), __byte_perm(w2, w3, 0x5410));
  mma16816(hi, a0, a2, __byte_perm(w0, w1, 0x7632), __byte_perm(w2, w3, 0x7632));
}
__device__ __forceinline__ void blk64(float (&acc)[8][4], uint32_t a0, uint32_t a2, const uint4 (&w)[4]) {
  mma_word(acc[0], acc[1], a0, a2, w[0].x, w[1].x, w[2].x, w[3].x);
  mma_word(acc[2], acc[3], a0, a2, w[0].y, w[1].y, w[2].y, w[3].y);
  mma_word(acc[4], acc[5], a0, a2, w[0].z, w[1].z, w[2].z, w[3].z);
  mma_word(acc[6], acc[7], a0, a2, w[0].w, w[1].w, w[2].w, w[3].w);
}
__device__ __forceinline__ void blk32(float (&acc)[4][4], uint32_t a0, uint32_t a2, const uint2 (&w)[4]) {
  mma_word(acc[0], acc[1], a0, a2, w[0].x, w[1].x, w[2].x, w[3].x);
  mma_word(acc[2], acc[3], a0, a2, w[0].y, w[1].y, w[2].y, w[3].y);
}
__device__ __forceinline__ void ldsm4t(uint32_t (&r)[4], uint32_t addr) {
  asm volatile("ldmatrix.sync.aligned.m8n8.x4.trans.shared.b16 {%0, %1, %2, %3}, [%4];"
               : "=r"(r[0]), "=r"(r[1]), "=r"(r[2]), "=r"(r[3]) : "r"(addr) : "memory");
}
__device__ __forceinline__ void mma_full(float (&c)[4], const uint32_t (&a)[4], uint32_t b0, uint32_t b1) {
  asm volatile(
      "mma.sync.aligned.m16n8k16.row.col.f32.bf16.bf16.f32 {%0,%1,%2,%3}, {%4,%5,%6,%7}, {%8,%9}, {%0,%1,%2,%3};"
      : "+f"(c[0]), "+f"(c[1]), "+f"(c[2]), "+f"(c[3])
      : "r"(a[0]), "r"(a[1]), "r"(a[2]), "r"(a[3]), "r"(b0), "r"(b1));
}
__device__ __forceinline__ int wpos(int u) { return (u & ~7) | ((u & 3) << 1) | ((u >> 2) & 1); }
__device__ __forceinline__ void put_frag(float* red, const float (&c)[4], int lane) {
  if ((lane & 3) < 2) {
    float* dst = red + (lane & 3) * 32 + (lane >> 2);
    dst[0] = c[0]; dst[16] = c[1]; dst[8] = c[2]; dst[24] = c[3];
  }
}
template <int NS, bool GENTLE, class F>
__device__ __forceinline__ void poll_frags(uint32_t (&bf)[NS][2], const unsigned long long* p, uint32_t tag, bool active,
                                           const unsigned* cnt_p, unsigned cnt_tight, F mid) {
  unsigned long long v0[NS], v1[NS];
  unsigned cnt = 0;
#pragma unroll
  for (int i = 0; i < NS; i++) v0[i] = v1[i] = (unsigned long long)tag << 32;
  auto issue = [&]() {
    if (GENTLE) cnt = ld_relaxed32(cnt_p);
#pragma unroll
    for (int i = 0; i < NS; i++)
      asm volatile("ld.relaxed.gpu.global.v2.u64 {%0, %1}, [%2];" : "=l"(v0[i]), "=l"(v1[i]) : "l"(p + i * 8) : "memory");
  };
  if (active) issue();
  __syncwarp();
  mid();
  int spin = 0;
  while (true) {
    uint32_t bad = 0, bi[NS];
#pragma unroll
    for (int i = 0; i < NS; i++) {
      bi[i] = ((uint32_t)(v0[i] >> 32) ^ tag) | ((uint32_t)(v1[i] >> 32) ^ tag);
      bad |= bi[i];
    }
    if (bad == 0 || ++spin > (1 << 22)) break;
    if (GENTLE && (int)(cnt - cnt_tight) < 0) __nanosleep(400);
    if (GENTLE) cnt = ld_relaxed32(cnt_p);
#pragma unroll
    for (int i = 0; i < NS; i++)
      asm volatile("{ .reg .pred p; setp.ne.u32 p, %3, 0; @p ld.relaxed.gpu.global.v2.u64 {%0, %1}, [%2]; }"
                   : "+l"(v0[i]), "+l"(v1[i]) : "l"(p + i * 8), "r"(bi[i]) : "memory");
  }
#pragma unroll
  for (int i = 0; i < NS; i++) {
    bf[i][0] = (uint32_t)v0[i];
    bf[i][1] = (uint32_t)v1[i];
  }
  __syncwarp();
}
template <int NS>
__device__ __forceinline__ void gemv_frags(float* red, const uint32_t (&wf)[NS][4], const uint32_t (&bf)[NS][2], int lane) {
  float acc[4][4];
#pragma unroll
  for (int i = 0; i < 4; i++)
#pragma unroll
    for (int k = 0; k < 4; k++) acc[i][k] = 0.f;
#pragma unroll
  for (int ks = 0; ks < NS; ks++) mma_full(acc[ks & 3], wf[ks], bf[ks][0], bf[ks][1]);
#pragma unroll
  for (int k = 0; k < 4; k++) acc[0][k] = (acc[0][k] + acc[1][k]) + (acc[2][k] + acc[3][k]);
  put_frag(red, acc[0], lane);
}
__device__ __forceinline__ void put_act_pair(uint8_t* row, int k, uint32_t v) {
  reinterpret_cast<uint16_t*>(row)[kperm(k)] = (uint16_t)v;
  reinterpret_cast<uint16_t*>(row)[kperm(k + 1)] = (uint16_t)(v >> 16);
}

__device__ __forceinline__ uint32_t bmul2(uint32_t a, uint32_t b) {
  uint32_t d;
  asm("mul.rn.bf16x2 %0, %1, %2;" : "=r"(d) : "r"(a), "r"(b));
  return d;
}
__device__ __forceinline__ uint32_t badd2(uint32_t a, uint32_t b) {
  uint32_t d;
  asm("add.rn.bf16x2 %0, %1, %2;" : "=r"(d) : "r"(a), "r"(b));
  return d;
}
__device__ __forceinline__ float rcp_fast(float x) {
  float r;
  asm("rcp.approx.ftz.f32 %0, %1;" : "=f"(r) : "f"(x));
  return r;
}
__device__ __forceinline__ float2 row_stats10(const float (&v)[10], float* s_tmp, int tid) {
  const int warp = tid >> 5, lane = tid & 31;
  float m = (((v[0] + v[1]) + (v[2] + v[3])) + ((v[4] + v[5]) + (v[6] + v[7])) + (v[8] + v[9])) * 0.1f;
  float q0 = 0.f, q1 = 0.f;
#pragma unroll
  for (int i = 0; i < 5; i++) {
    const float d0 = v[2 * i] - m, d1 = v[2 * i + 1] - m;
    q0 += d0 * d0;
    q1 += d1 * d1;
  }
  float q = q0 + q1;
#pragma unroll
  for (int k = 0; k < 5; k++) {
    const float mo = __shfl_xor_sync(0xffffffffu, m, 1 << k);
    const float qo = __shfl_xor_sync(0xffffffffu, q, 1 << k);
    const float dm = m - mo;
    q = (q + qo) + dm * dm * (float)(5 << k);
    m = 0.5f * (m + mo);
  }
  if (lane == 0) *reinterpret_cast<float2*>(s_tmp + 2 * warp) = make_float2(m, q);
  asm volatile("bar.sync %0, 64;" ::"r"(6 + (warp >> 1)) : "memory");
  const float4 t = *reinterpret_cast<const float4*>(s_tmp + 4 * (warp >> 1));
  const float mean = 0.5f * (t.x + t.z), dm = t.x - t.z;
  const float var = bf16r((t.y + t.w + dm * dm * (kD / 4)) * (1.0f / kD));
  return make_float2(bf16r(mean), bf16r(sqrt_fast(bf16r(var + 1e-5f))));
}

__global__ void __launch_bounds__(kThreads, 1)
fused_kernel(const __nv_bfloat16* __restrict__ x, const __nv_bfloat16* __restrict__ kc,
             const __nv_bfloat16* __restrict__ vc,
             const __nv_bfloat16* __restrict__ wo, const __nv_bfloat16* __restrict__ wg,
             const __nv_bfloat16* __restrict__ wu, const __nv_bfloat16* __restrict__ wd,
             const __nv_bfloat16* __restrict__ cvec, const __grid_constant__ CUtensorMap tm_wmod,
             const __grid_constant__ CUtensorMap tm_wq, __nv_bfloat16* __restrict__ out) {
  extern __shared__ __align__(1024) uint8_t smem[];
  const uint32_t sbase = (uint32_t)__cvta_generic_to_shared(smem);
  float* s_scores = reinterpret_cast<float*>(smem + kOffScores);
  float* s_x1 = reinterpret_cast<float*>(smem + kOffX1);
  float* s_small = reinterpret_cast<float*>(smem + kOffSmall);
  uint32_t* s_xb2 = reinterpret_cast<uint32_t*>(smem + kOffXb);
  const uint32_t bar_full = sbase + kOffBar;
  const uint32_t bar_empty = sbase + kOffBar + 8 * kNST;
  const uint32_t bar_wo = sbase + kOffBar + 16 * kNST;
  const uint32_t bar_wq = bar_wo + 8;
  const uint32_t bar_wm = bar_wo + 16;
  const uint32_t bar_gu = bar_wo + 24;
  const uint32_t bar_dn = bar_wo + 32;
  const uint32_t bar_open = bar_wo + 40;
  volatile uint32_t* s_dec = reinterpret_cast<volatile uint32_t*>(smem + kOffBar + 200);
  volatile uint32_t* s_ptag = reinterpret_cast<volatile uint32_t*>(smem + kOffBar + 196);
  volatile uint32_t* s_desc = reinterpret_cast<volatile uint32_t*>(smem + kOffBar + 160);
  volatile int* s_nown = reinterpret_cast<volatile int*>(smem + kOffBar + 192);

  const int cta = blockIdx.x;
  const int bb = cta >> 5, hh = cta & 31;
  if (threadIdx.x == 0) {
    for (int s = 0; s < kNST; s++) {
      mbar_init(bar_full + 8 * s, 1);
      mbar_init(bar_empty + 8 * s, kNCW);
    }
    mbar_init(bar_wo, 64);
    mbar_init(bar_wq, 1);
    mbar_init(bar_wm, 1);
    mbar_init(bar_gu, 64);
    mbar_init(bar_dn, 32);
    mbar_init(bar_open, 1);
    *s_nown = -1000;
    *s_dec = 0;
    asm volatile("fence.mbarrier_init.release.cluster;" ::: "memory");
  }
  __syncthreads();
  if (threadIdx.x == kNCT + 32 && cta < kNModCTA) {
    mbar_expect_tx(bar_wm, kD * 64);
#pragma unroll
    for (int i = 0; i < 5; i++) tma_load_2d(sbase + kOffWmod + i * 8192, &tm_wmod, cta * 32, i * 128, bar_wm);
  }

  if (threadIdx.x >= kNCT) {
    asm volatile("setmaxnreg.dec.sync.aligned.u32 56;");
    const int pw = (threadIdx.x - kNCT) >> 5, lane = threadIdx.x & 31;
    if (pw == 0) {
      asm volatile("bar.sync 2, 288;" ::: "memory");
      if (cta < kNQCTA) mbar_wait(bar_wq, 0);
      uint64_t pol_stream;
      asm volatile("createpolicy.fractional.L2::evict_first.b64 %0, 1.0;" : "=l"(pol_stream));
      int st = 0, ph = 0, lst = 0, lph = 0, it = 0, nl = 0, depth = kInflight;
      uint32_t ptag = 0;
      auto acquire_slot = [&]() {
        if (st >= kFreeSt) mbar_wait(bar_empty + 8 * st, ph);
        else if (it >= kNST) mbar_wait(bar_empty + 8 * st, ph ^ 1);
        while (it - nl >= depth) {
          mbar_wait(bar_full + 8 * lst, lph);
          if (++lst == kNST) { lst = 0; lph ^= 1; }
          nl++;
        }
      };
      if (lane == 0) {
        const uint8_t* kp = reinterpret_cast<const uint8_t*>(kc) + (size_t)cta * kSK * kDH * 2;
        const uint8_t* vp = reinterpret_cast<const uint8_t*>(vc) + (size_t)cta * kSK * kDH * 2;
        uint32_t cl = 0;
        uint32_t lid;
        asm volatile("mov.u32 %0, %laneid;" : "=r"(lid));
        uint32_t* my_claim = &g_claim[cta + lid];
        bool fin = false;
        uint32_t pc = 0;
        unsigned* my_prog = &g_prog[lid];
        int have = kFirstClaim;
#pragma unroll 1
        for (;; it++) {
          if (it == have && !fin) {
            if (it == kFirstClaim) {
              mbar_wait(bar_open, 0);
              ptag = *s_ptag;
            }
            const int got = min(kChunk, kS - cl_front(cl) - cl_stolen(cl));
            if (got > 0) have += got;
            fin = !(got == kChunk && have < kTotTiles);
            if (fin) *s_nown = have - kFirstClaim;
            asm volatile("{ .reg .pred p; setp.eq.u32 p, %3, 0; @p atom.relaxed.gpu.global.add.u32 %0, [%1], %2; }"
                         : "+r"(cl) : "l"(my_claim), "r"(kChunk), "r"((uint32_t)fin) : "memory");
          }
          if ((it & 1) == 0) {
            if (it >= kPaceStart) {
              const int d = (it - 1) * kNCTA - (int)pc;
              depth = d > kPaceT ? kInflight - 1 : (d < -kPaceT ? kInflight + 1 : kInflight);
            }
            asm volatile("atom.relaxed.gpu.global.add.u32 %0, [%1], 2;" : "+r"(pc) : "l"(my_prog) : "memory");
          }
          acquire_slot();
          if (it == have) break;
          const uint8_t* src = (it < kKTiles) ? kp + (size_t)it * kTileBytes : vp + (size_t)(it - kKTiles) * kTileBytes;
          s_desc[st] = (uint32_t)(it - kKTiles);
          mbar_expect_tx(bar_full + 8 * st, kTileBytes);
          bulk_load(sbase + kOffRing + st * kTileBytes, src, kTileBytes, bar_full + 8 * st, pol_stream);
          if (++st == kNST) { st = 0; ph ^= 1; }
        }
      }
      depth = kInflight;
      ptag = __shfl_sync(0xffffffffu, ptag, 0);
      const int nround = wait_dec(s_dec) == 1 ? 0 : 4 * kS;
#pragma unroll 1
      for (int round = 0; round < nround; round++) {
        const uint32_t best = scan_claims(ptag, cta, lane);
        const int r = (int)(best >> 16);
        if (r < kMinR) break;
        if (lane == 0) {
          const int victim = best & 127;
          const int k = min(kMaxTake, (r - kMinR) / 2 + 1);
          uint32_t o;
          asm volatile("atom.acquire.gpu.global.add.u32 %0, [%1], %2;" : "=r"(o) : "l"(&g_claim[victim]), "r"(k << 8) : "memory");
          const int stolen = cl_stolen(o);
          const int got = min(k, kS - cl_front(o) - stolen);
          asm volatile("fence.proxy.async.global;" ::: "memory");
#pragma unroll 1
          for (int i = 0; i < got; i++) {
            const int rel = kS - 1 - stolen - i;
            s_desc[st] = kDescSteal | (uint32_t)(victim * kS + rel);
            mbar_expect_tx(bar_full + 8 * st, kTileBytes + 128);
            bulk_load(sbase + kOffRing + st * kTileBytes,
                      reinterpret_cast<const uint8_t*>(vc) + ((size_t)victim * kKTiles + (kKTiles - kS) + rel) * kTileBytes, kTileBytes,
                      bar_full + 8 * st, pol_stream);
            bulk_load(sbase + kOffPst + st * 128, &g_p[(victim * kS + rel) * kTileKeys], 128, bar_full + 8 * st, pol_stream);
            if (++st == kNST) { st = 0; ph ^= 1; }
            it++;
            acquire_slot();
          }
        }
        __syncwarp();
      }
      if (lane == 0) {
        s_desc[st] = kDescEnd;
        mbar_arrive(bar_full + 8 * st);
      }
    } else {
      if (pw == 1 && lane == 0) {
        if (cta < kNQCTA) {
          __nanosleep(600);
          mbar_expect_tx(bar_wq, kD * 128);
#pragma unroll 1
          for (int i = 0; i < 5; i++) tma_load_2d(sbase + kOffWq + i * 16384, &tm_wq, cta * 64, i * 128, bar_wq);
        }
      }
      if (pw >= 2 && cta < kNQCTA) mbar_wait(bar_wq, 0);
      if (pw >= 2 && cta >= kNQCTA && cta < kNModCTA) mbar_wait(bar_wm, 0);
      constexpr int kWoHead = (kOffWmod - kOffWo) / 32;
      const __nv_bfloat16* wo_src = wo + (size_t)(cta / 40) * kWoK * kD + (cta % 40) * 16;
      if (pw == 3 && cta < kNWCTA) {
        asm volatile("bar.sync 4, 288;" ::: "memory");
        slice_load<4, 100>(sbase + kOffWo + kWoHead * 32, wo_src + (size_t)kWoHead * kD, kD, kWoK - kWoHead, bar_wo, lane);
      }
      if (pw == 1) {
        asm volatile("bar.sync 3, 288;" ::: "memory");
        if (cta < kNWCTA) slice_load<8, 0>(sbase + kOffWo, wo_src, kD, kWoHead, bar_wo, lane);
      }
      __syncwarp();
      {
        const int gt = threadIdx.x - kNCT - 32;
        const uint32_t ptag = *reinterpret_cast<volatile unsigned*>(&g_epoch) + 1u;
        asm volatile("bar.sync 11, 352;" ::: "memory");
        if (gt == 0) {
          asm volatile("fence.acq_rel.gpu;" ::: "memory");
          asm volatile("st.relaxed.gpu.global.u32 [%0], %1;" ::"l"(&g_claim[cta]), "r"((ptag << 20) | kChunk) : "memory");
          *s_ptag = ptag;
          mbar_arrive(bar_open);
        }
        __syncwarp();
        asm volatile("bar.sync 12, 352;" ::: "memory");
        float a0 = 0.f, a1 = 0.f;
        int t = kS;
#pragma unroll 1
        for (int spin = 0; spin < (1 << 20); spin++) {
          const int nown = *s_nown;
          int lim = nown;
          if (nown >= 0 && pw == 3) {
            const uint32_t best = scan_claims(ptag, cta, lane);
            if (lane == 0) *s_dec = ((int)(best >> 16) >= kMinR) ? 2u : 1u;
          }
          if (nown < 0) {
            const uint32_t w = ld_relaxed32(&g_claim[cta]);
            lim = (((w ^ (ptag << 20)) >> 20) == 0 && cl_front(w) + cl_stolen(w) <= kS) ? kS - cl_stolen(w) : kS;
          }
#pragma unroll 1
          while (t > lim) {
            const int nb = min(4, t - lim);
            unsigned long long v0[4], v1[4];
            int sp2 = 0;
            uint32_t bad;
            do {
              bad = 0;
#pragma unroll
              for (int i = 0; i < 4; i++)
                asm volatile("ld.relaxed.gpu.global.v2.u64 {%0, %1}, [%2];" : "=l"(v0[i]), "=l"(v1[i])
                             : "l"(&g_part[(cta * kS + t - 1 - min(i, nb - 1)) * kDH + 2 * gt]) : "memory");
#pragma unroll
              for (int i = 0; i < 4; i++) bad |= ((uint32_t)(v0[i] >> 32) ^ ptag) | ((uint32_t)(v1[i] >> 32) ^ ptag);
            } while (bad != 0 && ++sp2 < (1 << 18));
#pragma unroll
            for (int i = 0; i < 4; i++)
              if (i < nb) {
                a0 += __uint_as_float((uint32_t)v0[i]);
                a1 += __uint_as_float((uint32_t)v1[i]);
              }
            t -= nb;
          }
          if (nown >= 0) break;
          __nanosleep(100);
        }
        asm volatile("bar.sync 10, 352;" ::: "memory");
        const float* s_own = reinterpret_cast<const float*>(smem + kOffAct);
#pragma unroll
        for (int w = 0; w < kNCW; w++) {
          const float2 v = *reinterpret_cast<const float2*>(s_own + w * kDH + gt * 2);
          a0 += v.x; a1 += v.y;
        }
        put_tagged(&g_ot[cta * (kDH / 2) + wpos(gt)], ptag, pack_bf16(a0, a1));
        if (gt == 95) hint_cnt(kCntV);
        if (pw >= 2 && cta < kNFCTA) slice_load<4, 100>(sbase + (pw == 2 ? kOffWg : kOffWu), (pw == 2 ? wg : wu) + cta * 16, kF, kD, bar_gu, lane);
      }
      if (pw == 1) {
        asm volatile("bar.sync 5, 288;" ::: "memory");
        if (cta < kNDCTA) slice_load<8, 20>(sbase + kOffWd, wd + cta * 16, kD, kF, bar_dn, lane);
      }
    }
    return;
  }

  asm volatile("setmaxnreg.inc.sync.aligned.u32 224;");
  const int tid = threadIdx.x;
  const int warp = tid >> 5, lane = tid & 31;
  STAMP(0);
  const int mr = lane & 3, mc = lane >> 2;
  const uint32_t act_frag = sbase + kOffAct + (mc & 3) * kActPitch + mr * 4;
  const int rowb = tid >> 6, rowi = tid & 63;
  uint8_t* arow = smem + kOffAct + rowb * kActPitch;

  uint32_t c2[5], x2[5];
#pragma unroll
  for (int i = 0; i < 5; i++) {
    c2[i] = reinterpret_cast<const uint32_t*>(cvec)[rowb * (kD / 2) + rowi + 64 * i];
    x2[i] = reinterpret_cast<const uint32_t*>(x)[rowb * (kD / 2) + rowi + 64 * i];
  }
  const uint32_t tag = *reinterpret_cast<volatile unsigned*>(&g_epoch) + 1u;
  x2[0] |= tag & (uint32_t)reinterpret_cast<uintptr_t>(x) & 1u;
  float xv[10];
#pragma unroll
  for (int i = 0; i < 5; i++) {
    const float c0 = bflo(c2[i]), c1 = bfhi(c2[i]);
    put_act_pair(arow, 2 * (rowi + 64 * i),
                 pack_bf16(__fdividef(c0, 1.0f + __expf(-c0)), __fdividef(c1, 1.0f + __expf(-c1))));
    s_xb2[rowb * (kD / 2) + rowi + 64 * i] = x2[i];
    xv[2 * i] = bflo(x2[i]);
    xv[2 * i + 1] = bfhi(x2[i]);
  }
  {
    const float2 st2 = row_stats10(xv, s_small, tid);
#pragma unroll
    for (int i = 0; i < 10; i++) xv[i] = bf16r(__fdividef(bf16r(xv[i] - st2.x), st2.y));
  }
  cbar();
  if (cta < kNModCTA) {
    mbar_wait(bar_wm, 0);
  }
  asm volatile("bar.arrive 2, 288;" ::: "memory");
  if (cta < kNModCTA) {
    float acc[4][4];
#pragma unroll
    for (int i = 0; i < 4; i++)
#pragma unroll
      for (int k = 0; k < 4; k++) acc[i][k] = 0.f;
#pragma unroll 1
    for (int ks = 0; ks < 5; ks++) {
      const int kb = (warp * 5 + ks) * 16;
      uint2 w[4];
#pragma unroll
      for (int t = 0; t < 4; t++) {
        const uint32_t a = sbase + kOffWmod + (kb + 4 * t + mr) * 64 + mc * 8;
        w[t] = lds64(a ^ (((a >> 7) & 3) << 4));
      }
      blk32(acc, lds32(act_frag + kb * 2), lds32(act_frag + kb * 2 + 16), w);
    }
    if (mc < 4) {
      float4* red = reinterpret_cast<float4*>(s_scores + warp * 128 + mc * 32 + mr * 8);
      red[0] = make_float4(acc[0][0], acc[1][0], acc[2][0], acc[3][0]);
      red[1] = make_float4(acc[0][1], acc[1][1], acc[2][1], acc[3][1]);
    }
  }
  cbar();
  if (cta < kNModCTA && tid < 64) {
    float2 s = make_float2(0.f, 0.f);
#pragma unroll
    for (int w = 0; w < kNCW; w++) {
      const float2 v = *reinterpret_cast<const float2*>(s_scores + w * 128 + tid * 2);
      s.x += v.x; s.y += v.y;
    }
    put_tagged(&g_modt[(tid >> 4) * (3 * kD) + cta * 16 + (tid & 15)], tag, pack_bf16(s.x, s.y));
  }
  if (cta < kNWCTA) asm volatile("bar.arrive 4, 288;" ::: "memory");
  STAMP(1);

  auto release_wq = [&]() {
    asm volatile("fence.proxy.async.shared::cta;" ::: "memory");
    __syncwarp();
    if (lane == 0) {
#pragma unroll
      for (int s = kFreeSt; s < kNST; s++) mbar_arrive(bar_empty + 8 * s);
    }
  };
  if (cta >= kNQCTA) release_wq();
  if (cta < kNQCTA) {
    {
      uint32_t sc10[10];
      __nanosleep(800);
      get_tagged<10>(sc10, &g_modt[rowb * (3 * kD) + rowi], 64, tag);
      const uint32_t* sa = sc10;
      const uint32_t* ca = sc10 + 5;
#pragma unroll
      for (int i = 0; i < 5; i++)
        put_act_pair(arow, 2 * (rowi + 64 * i),
                     pack_bf16(bf16r(xv[2 * i] * bf16r(1.0f + bflo(ca[i]))) + bflo(sa[i]),
                               bf16r(xv[2 * i + 1] * bf16r(1.0f + bfhi(ca[i]))) + bfhi(sa[i])));
    }
    cbar();
    float acc[8][4];
#pragma unroll
    for (int i = 0; i < 8; i++)
#pragma unroll
      for (int k = 0; k < 4; k++) acc[i][k] = 0.f;
    mbar_wait(bar_wq, 0);
#pragma unroll 1
    for (int ks = 0; ks < 5; ks++) {
      const int kb = (warp * 5 + ks) * 16;
      uint4 w[4];
#pragma unroll
      for (int t = 0; t < 4; t++) {
        const uint32_t a = sbase + kOffWq + (kb + 4 * t + mr) * 128 + mc * 16;
        w[t] = lds128(a ^ (((a >> 7) & 7) << 4));
      }
      blk64(acc, lds32(act_frag + kb * 2), lds32(act_frag + kb * 2 + 16), w);
    }
    release_wq();
    if (mc < 4) {
      float4* red = reinterpret_cast<float4*>(s_scores + warp * 256 + mc * 64 + mr * 16);
      red[0] = make_float4(acc[0][0], acc[1][0], acc[2][0], acc[3][0]);
      red[1] = make_float4(acc[4][0], acc[5][0], acc[6][0], acc[7][0]);
      red[2] = make_float4(acc[0][1], acc[1][1], acc[2][1], acc[3][1]);
      red[3] = make_float4(acc[4][1], acc[5][1], acc[6][1], acc[7][1]);
    }
    cbar();
    if (tid < 128) {
      float2 s = make_float2(0.f, 0.f);
#pragma unroll
      for (int w = 0; w < kNCW; w++) {
        const float2 v = *reinterpret_cast<const float2*>(s_scores + w * 256 + tid * 2);
        s.x += v.x; s.y += v.y;
      }
      put_tagged(&g_qt[(tid >> 5) * (kH * kDH / 2) + cta * 32 + (tid & 31)], tag, pack_bf16(s.x, s.y));
    }
  }
  STAMP(2);

  const int j = lane & 7, g = lane >> 3;
  {
    float oa[24];
    uint32_t gav[5], sbv[5], cbv[5], gbv[1];
    uint32_t wof[16][4], wgf[5][4], wuf[5][4];
    const uint32_t lm_w = ((lane & 7) + (lane >> 4) * 8) * 32 + ((((lane >> 3) ^ (lane >> 2)) & 1) << 4);
#pragma unroll
    for (int i = 0; i < 24; i++) oa[i] = 0.f;
    {
      if (tid < kDH / 2) {
        uint32_t qv[1];
        if (cta < kNQCTA) __nanosleep(500);
        get_tagged<1>(qv, &g_qt[bb * (kH * kDH / 2) + hh * (kDH / 2) + tid], 0, tag);
        *reinterpret_cast<float2*>(s_small + 32 + 2 * tid) = make_float2(bflo(qv[0]), bfhi(qv[0]));
      }
      cbar();
      STAMP(3);
      float qf[24];
#pragma unroll
      for (int i = 0; i < 3; i++)
#pragma unroll
        for (int e = 0; e < 8; e += 4) {
          const float4 v = *reinterpret_cast<const float4*>(s_small + 32 + (j + 8 * i) * 8 + e);
          qf[i * 8 + e] = v.x; qf[i * 8 + e + 1] = v.y; qf[i * 8 + e + 2] = v.z; qf[i * 8 + e + 3] = v.w;
        }

      const float scale = 0.07216878364870322f;
      float lmax = -INFINITY;
      int it = 0, st = 0, ph = 0;
#pragma unroll 1
      for (; it < kKTiles; it++) {
        if (it == 4) {
      if (cta < kNFCTA) {
        const unsigned long long* pm = &g_modt[rowb * (3 * kD) + 2 * (kD / 2) + rowi];
        const unsigned long long* pg = &g_modt[((tid >> 3) & 3) * (3 * kD) + 5 * (kD / 2) + (cta % kNDCTA) * 8 + (tid & 7)];
        int spin = 0;
        bool ok;
        do {
          ok = true;
#pragma unroll
          for (int i = 0; i < 5; i++) {
            const unsigned long long v0 = ld_relaxed64(pm + i * 64), v1 = ld_relaxed64(pm + kD / 2 + i * 64),
                                     v2 = ld_relaxed64(pm + kD + i * 64);
            gav[i] = (uint32_t)v0; sbv[i] = (uint32_t)v1; cbv[i] = (uint32_t)v2;
            ok = ok && ((uint32_t)(v0 >> 32) == tag) && ((uint32_t)(v1 >> 32) == tag) && ((uint32_t)(v2 >> 32) == tag);
          }
          const unsigned long long v3 = ld_relaxed64(pg);
          gbv[0] = (uint32_t)v3;
          ok = ok && ((uint32_t)(v3 >> 32) == tag);
        } while (!ok && ++spin < (1 << 22));
      }
      asm volatile("bar.arrive 3, 288;" ::: "memory");
        }
        mbar_wait(bar_full + 8 * st, ph);
        const uint32_t base = sbase + kOffRing + st * kTileBytes + (warp * 8 + g) * (kDH * 2) + j * 16;
        uint4 kv[2][3];
#pragma unroll
        for (int u = 0; u < 2; u++)
#pragma unroll
          for (int i = 0; i < 3; i++) kv[u][i] = lds128(base + u * 4 * (kDH * 2) + i * 128);
        float sc[2];
#pragma unroll
        for (int u = 0; u < 2; u++) {
          float a0 = 0.f, a1 = 0.f;
#pragma unroll
          for (int i = 0; i < 3; i++) {
            a0 += qf[i * 8 + 0] * bflo(kv[u][i].x); a1 += qf[i * 8 + 1] * bfhi(kv[u][i].x);
            a0 += qf[i * 8 + 2] * bflo(kv[u][i].y); a1 += qf[i * 8 + 3] * bfhi(kv[u][i].y);
            a0 += qf[i * 8 + 4] * bflo(kv[u][i].z); a1 += qf[i * 8 + 5] * bfhi(kv[u][i].z);
            a0 += qf[i * 8 + 6] * bflo(kv[u][i].w); a1 += qf[i * 8 + 7] * bfhi(kv[u][i].w);
          }
          sc[u] = a0 + a1;
        }
        __syncwarp();
        if (lane == 0) mbar_arrive(bar_empty + 8 * st);
        if (++st == kNST) { st = 0; ph ^= 1; }
#pragma unroll
        for (int m = 1; m < 8; m <<= 1) {
          sc[0] += __shfl_xor_sync(0xffffffffu, sc[0], m);
          sc[1] += __shfl_xor_sync(0xffffffffu, sc[1], m);
        }
#pragma unroll
        for (int u = 0; u < 2; u++) {
          const float s = bf16r(bf16r(sc[u]) * scale);
          lmax = fmaxf(lmax, s);
          if (j == 0) s_scores[it * kTileKeys + warp * 8 + u * 4 + g] = s;
        }
      }
      STAMP(4);
#pragma unroll
      for (int m = 16; m > 0; m >>= 1) lmax = fmaxf(lmax, __shfl_xor_sync(0xffffffffu, lmax, m));
      if (lane == 0) s_small[warp] = lmax;
      cbar();
      {
        float gmax = s_small[0];
#pragma unroll
        for (int w = 1; w < kNCW; w++) gmax = fmaxf(gmax, s_small[w]);
        float ev[16];
        float lsum = 0.f;
#pragma unroll
        for (int i = 0; i < 16; i++) {
          ev[i] = __expf(s_scores[tid + kNCT * i] - gmax);
          lsum += ev[i];
        }
#pragma unroll
        for (int m = 16; m > 0; m >>= 1) lsum += __shfl_xor_sync(0xffffffffu, lsum, m);
        if (lane == 0) s_small[8 + warp] = lsum;
        cbar();
        float gsum = 0.f;
#pragma unroll
        for (int w = 0; w < kNCW; w++) gsum += s_small[8 + w];
        const float inv = __fdividef(1.0f, gsum);
#pragma unroll
        for (int i = 0; i < 16; i++) {
          const __nv_bfloat16 pb = __float2bfloat16_rn(ev[i] * inv);
          s_scores[tid + kNCT * i] = __bfloat162float(pb);
          if (i >= 16 - kS / 4) g_p[cta * (kS * kTileKeys) + tid + kNCT * (i - (16 - kS / 4))] = pb;
        }
      }
      asm volatile("bar.arrive 11, 352;" ::: "memory");
      if (cta < kNWCTA) {
        mbar_wait(bar_wo, 0);
#pragma unroll
        for (int ks = 0; ks < 16; ks++) ldsm4t(wof[ks], sbase + kOffWo + (warp * 16 + ks) * 512 + lm_w);
      }
      cbar();
      STAMP(5);
      uint32_t desc = kDescEnd;
#pragma unroll 1
      for (int n = 0; n <= kKTiles; n++) {
        mbar_wait(bar_full + 8 * st, ph);
        desc = s_desc[st];
        if (desc >= kDescSteal) break;
        const uint32_t base = sbase + kOffRing + st * kTileBytes + (warp * 8 + g) * (kDH * 2) + j * 16;
        uint4 vv[2][3];
#pragma unroll
        for (int u = 0; u < 2; u++)
#pragma unroll
          for (int i = 0; i < 3; i++) vv[u][i] = lds128(base + u * 4 * (kDH * 2) + i * 128);
        float p[2];
#pragma unroll
        for (int u = 0; u < 2; u++) p[u] = s_scores[desc * kTileKeys + warp * 8 + u * 4 + g];
#pragma unroll
        for (int u = 0; u < 2; u++)
#pragma unroll
          for (int i = 0; i < 3; i++) fma8(oa + 8 * i, vv[u][i], p[u]);
        __syncwarp();
        if (lane == 0) mbar_arrive(bar_empty + 8 * st);
        if (desc == kKTiles - kS - 1) asm volatile("bar.arrive 12, 352;" ::: "memory");
        if (++st == kNST) { st = 0; ph ^= 1; }
        if ((int)desc + 1 - (kKTiles - kS) == *s_nown) break;
      }

      auto reduce_warp = [&](float* s_ored) {
        const bool h16 = (lane & 16) != 0, h8 = (lane & 8) != 0;
        float r1[12];
#pragma unroll
        for (int i = 0; i < 12; i++) {
          const float lo = oa[(i >> 2) * 8 + (i & 3)], hi = oa[(i >> 2) * 8 + 4 + (i & 3)];
          r1[i] = (h16 ? hi : lo) + __shfl_xor_sync(0xffffffffu, h16 ? lo : hi, 16);
        }
#pragma unroll
        for (int i = 0; i < 3; i++) {
          float r2[2];
#pragma unroll
          for (int e = 0; e < 2; e++) {
            const float lo = r1[i * 4 + e], hi = r1[i * 4 + 2 + e];
            r2[e] = (h8 ? hi : lo) + __shfl_xor_sync(0xffffffffu, h8 ? lo : hi, 8);
          }
          *reinterpret_cast<float2*>(s_ored + warp * kDH + (j + 8 * i) * 8 + (g >> 1) * 4 + (g & 1) * 2) = make_float2(r2[0], r2[1]);
        }
      };
      auto reduce_cta = [&](const float* s_ored) {
        float2 s = make_float2(0.f, 0.f);
#pragma unroll
        for (int w = 0; w < kNCW; w++) {
          const float2 v = *reinterpret_cast<const float2*>(s_ored + w * kDH + tid * 2);
          s.x += v.x; s.y += v.y;
        }
        return s;
      };
      reduce_warp(reinterpret_cast<float*>(smem + kOffAct));
      STAMP(6);
      asm volatile("bar.arrive 10, 352;" ::: "memory");
      if (desc < kDescSteal) {
        if (wait_dec(s_dec) == 1) {
          desc = kDescEnd;
        } else {
          mbar_wait(bar_full + 8 * st, ph);
          desc = s_desc[st];
        }
      }
      int rb = 1;
#pragma unroll 1
      for (int n = 0; n < 16 * kS && desc != kDescEnd; n++) {
        const uint32_t base = sbase + kOffRing + st * kTileBytes + (warp * 8 + g) * (kDH * 2) + j * 16;
        uint4 vv[2][3];
#pragma unroll
        for (int u = 0; u < 2; u++)
#pragma unroll
          for (int i = 0; i < 3; i++) vv[u][i] = lds128(base + u * 4 * (kDH * 2) + i * 128);
        float p[2];
#pragma unroll
        for (int u = 0; u < 2; u++)
          p[u] = __bfloat162float(reinterpret_cast<const __nv_bfloat16*>(smem + kOffPst + st * 128)[warp * 8 + u * 4 + g]);
#pragma unroll
        for (int i = 0; i < 24; i++) oa[i] = 0.f;
#pragma unroll
        for (int u = 0; u < 2; u++)
#pragma unroll
          for (int i = 0; i < 3; i++) fma8(oa + 8 * i, vv[u][i], p[u]);
        __syncwarp();
        if (lane == 0) mbar_arrive(bar_empty + 8 * st);
        if (++st == kNST) { st = 0; ph ^= 1; }
        float* s_rb = rb ? reinterpret_cast<float*>(smem + kOffAct) + kNCW * kDH : s_scores;
        reduce_warp(s_rb);
        cbar();
        if (tid < kDH / 2) {
          const float2 s = reduce_cta(s_rb);
          const unsigned long long t64 = (unsigned long long)tag << 32;
          asm volatile("st.relaxed.gpu.global.v2.u64 [%0], {%1, %2};" ::"l"(&g_part[(desc & 0x7fffu) * kDH + 2 * tid]),
                       "l"(t64 | __float_as_uint(s.x)), "l"(t64 | __float_as_uint(s.y)) : "memory");
        }
        rb ^= 1;
        mbar_wait(bar_full + 8 * st, ph);
        desc = s_desc[st];
      }
    }
    if (cta >= kNDCTA) asm volatile("bar.arrive 5, 288;" ::: "memory");
    if (cta >= kNWCTA) return;
    cbar();

    uint32_t wdf[12][4];
    {
      uint32_t bf[16][2];
      poll_frags<16, true>(bf, &g_ot[(mc & 3) * (kH * kDH / 2) + (cta / 40) * (kWoK / 2) + warp * 128 + mr * 2], tag, mc < 4,
                           &g_cnt[kCntV * 32], tag * kNCTA - 32, []() {});
      STAMP(7);
      if (cta < kNDCTA) asm volatile("bar.arrive 5, 288;" ::: "memory");
      gemv_frags<16>(s_scores + 2048 + warp * 64, wof, bf, lane);
      cbar();
      if (tid == 64) hint_cnt(kCntY);
      if (tid < 64) {
        float sy = 0.f;
#pragma unroll
        for (int w = 0; w < kNCW; w++) sy += s_scores[2048 + w * 64 + tid];
        uint32_t yb = __float_as_uint(sy);
        yb = ((uint32_t)max((int)min(yb & 0x7fffffffu, 0x7fc00000u) + (0x80 - (int)(tag & 0xffu)), 0) & 0xffffff00u) | (yb & 0x80000000u);
        asm volatile("st.relaxed.gpu.global.u32 [%0], %1;" ::"l"(&g_yt[((cta / 40) * kB + (tid >> 4)) * kD + (cta % 40) * 16 + (tid & 15)]),
                     "r"(yb | (tag & 0xffu)) : "memory");
      }
    }
    STAMP(8);
    if (cta >= kNFCTA) return;
    auto load_gu = [&]() {
      mbar_wait(bar_gu, 0);
#pragma unroll
      for (int ks = 0; ks < 5; ks++) {
        ldsm4t(wgf[ks], sbase + kOffWg + (warp * 5 + ks) * 512 + lm_w);
        ldsm4t(wuf[ks], sbase + kOffWu + (warp * 5 + ks) * 512 + lm_w);
      }
    };
    if (warp != 0) load_gu();

    {
      uint32_t x1p[5], c1p[5];
#pragma unroll
      for (int i = 0; i < 5; i++) {
        x1p[i] = s_xb2[rowb * (kD / 2) + rowi + 64 * i];
        c1p[i] = badd2(0x3f803f80u, cbv[i]);
      }
      if (tid == 0) {
        wait_cnt(kCntY, tag * kNWCTA);
        if (cta == 0) { g_epoch = tag; g_prog[0] = 0; }
      }
      cbar();
      STAMP(9);
      {
        const uint32_t* py = &g_yt[rowb * kD + 2 * rowi];
        uint2 yv[15];
        int spin = 0;
        while (true) {
#pragma unroll
          for (int i = 0; i < 15; i++)
            asm volatile("ld.relaxed.gpu.global.v2.u32 {%0, %1}, [%2];" : "=r"(yv[i].x), "=r"(yv[i].y)
                         : "l"(py + (i / 5) * (kB * kD) + (i % 5) * 128) : "memory");
          if (warp == 0 && spin == 0) load_gu();
          uint32_t bd[5];
#pragma unroll
          for (int i = 0; i < 5; i++) {
            uint32_t b3[3];
#pragma unroll
            for (int k = 0; k < 3; k++)
              asm("lop3.b32 %0, %1, %2, %3, 0x7e;" : "=r"(b3[k]) : "r"(yv[3 * i + k].x), "r"(tag), "r"(yv[3 * i + k].y));
            asm("lop3.b32 %0, %1, %2, %3, 0xfe;" : "=r"(bd[i]) : "r"(b3[0]), "r"(b3[1]), "r"(b3[2]));
          }
          asm("lop3.b32 %0, %1, %2, %3, 0xfe;" : "=r"(bd[0]) : "r"(bd[0]), "r"(bd[1]), "r"(bd[2]));
          if (((bd[0] | bd[3] | bd[4]) & 0xffu) == 0 || ++spin > (1 << 22)) break;
        }
#pragma unroll
        for (int i = 0; i < 5; i++) {
          const float ya = (__uint_as_float(yv[i].x) + __uint_as_float(yv[5 + i].x)) + __uint_as_float(yv[10 + i].x);
          const float yb = (__uint_as_float(yv[i].y) + __uint_as_float(yv[5 + i].y)) + __uint_as_float(yv[10 + i].y);
          x1p[i] = badd2(x1p[i], bmul2(gav[i], pack_bf16(ya, yb)));
        }
      }
      float x1[10];
#pragma unroll
      for (int i = 0; i < 5; i++) {
        x1[2 * i] = bflo(x1p[i]);
        x1[2 * i + 1] = bfhi(x1p[i]);
        const int u = rowi + 64 * i;
        if ((u >> 3) == cta) *reinterpret_cast<float2*>(s_x1 + rowb * 16 + 2 * (u & 7)) = make_float2(x1[2 * i], x1[2 * i + 1]);
      }
      const float2 st2 = row_stats10(x1, s_small, tid);
      const uint32_t nmean = pack_bf16(-st2.x, -st2.x);
      const float rstd = rcp_fast(st2.y);
#pragma unroll
      for (int i = 0; i < 5; i++) {
        const uint32_t hc = badd2(x1p[i], nmean);
        reinterpret_cast<uint32_t*>(arow)[wpos(rowi) + 64 * i] = badd2(bmul2(pack_bf16(bflo(hc) * rstd, bfhi(hc) * rstd), c1p[i]), sbv[i]);
      }
    }
    cbar();
    STAMP(13);
    {
      float ag[2][4], au[2][4];
#pragma unroll
      for (int i = 0; i < 2; i++)
#pragma unroll
        for (int k = 0; k < 4; k++) ag[i][k] = au[i][k] = 0.f;
      const uint32_t ha = sbase + kOffAct + (mc & 3) * kActPitch + warp * 160 + mr * 8;
#pragma unroll
      for (int ks = 0; ks < 5; ks++) {
        const uint2 hb = lds64(ha + ks * 32);
        mma_full(ag[ks & 1], wgf[ks], hb.x, hb.y);
        mma_full(au[ks & 1], wuf[ks], hb.x, hb.y);
      }
#pragma unroll
      for (int k = 0; k < 4; k++) { ag[0][k] += ag[1][k]; au[0][k] += au[1][k]; }
      put_frag(s_scores + warp * 128, ag[0], lane);
      put_frag(s_scores + warp * 128 + 64, au[0], lane);
    }
    cbar();
    STAMP(14);
    if (tid < 32) {
      const int b = tid >> 3, cp = tid & 7;
      float2 gs = make_float2(0.f, 0.f), us = make_float2(0.f, 0.f);
#pragma unroll
      for (int w = 0; w < kNCW; w++) {
        const float2 gv = *reinterpret_cast<const float2*>(s_scores + w * 128 + tid * 2);
        const float2 uv = *reinterpret_cast<const float2*>(s_scores + w * 128 + 64 + tid * 2);
        gs.x += gv.x; gs.y += gv.y; us.x += uv.x; us.y += uv.y;
      }
      const uint32_t av = pack_bf16(bf16r(gelu_tanh(bf16r(gs.x))) * bf16r(us.x), bf16r(gelu_tanh(bf16r(gs.y))) * bf16r(us.y));
      put_tagged(&g_actt[b * (kF / 2) + cta * 8 + wpos(cp)], tag | 0x80000000u, av);
    }
    STAMP(10);
    if (cta >= kNDCTA) return;
    mbar_wait(bar_dn, 0);
#pragma unroll
    for (int ks = 0; ks < 12; ks++) ldsm4t(wdf[ks], sbase + kOffWd + (warp * 12 + ks) * 512 + lm_w);
    cbar();

    {
      uint32_t bf[12][2];
      poll_frags<12, false>(bf, &g_actt[(mc & 3) * (kF / 2) + warp * 96 + mr * 2], tag | 0x80000000u, mc < 4, nullptr, 0u, []() {});
      STAMP(11);
      gemv_frags<12>(s_scores + 2048 + warp * 64, wdf, bf, lane);
      cbar();
      if (tid < 32) {
        float2 s = make_float2(0.f, 0.f);
#pragma unroll
        for (int w = 0; w < kNCW; w++) {
          const float2 v = *reinterpret_cast<const float2*>(s_scores + 2048 + w * 64 + tid * 2);
          s.x += v.x; s.y += v.y;
        }
        const int b = tid >> 3, d = cta * 16 + (tid & 7) * 2;
        const float2 x1 = *reinterpret_cast<const float2*>(s_x1 + tid * 2);
        const uint32_t ov = pack_bf16(x1.x + bf16r(bflo(gbv[0]) * bf16r(s.x)), x1.y + bf16r(bfhi(gbv[0]) * bf16r(s.y)));
        reinterpret_cast<uint32_t*>(out)[(b * kD + d) / 2] = ov;
      }
    }
    STAMP(12);
  }
}

}

extern "C" void kernel_launch(void* const* d_in, const int* in_sizes, int n_in, void* d_out, int out_size) {
  const __nv_bfloat16* x = (const __nv_bfloat16*)d_in[0];
  const __nv_bfloat16* kc = (const __nv_bfloat16*)d_in[1];
  const __nv_bfloat16* vc = (const __nv_bfloat16*)d_in[2];
  const __nv_bfloat16* wq = (const __nv_bfloat16*)d_in[3];
  const __nv_bfloat16* wo = (const __nv_bfloat16*)d_in[4];
  const __nv_bfloat16* wg = (const __nv_bfloat16*)d_in[6];
  const __nv_bfloat16* wu = (const __nv_bfloat16*)d_in[7];
  const __nv_bfloat16* wd = (const __nv_bfloat16*)d_in[8];
  const __nv_bfloat16* cv = (const __nv_bfloat16*)d_in[9];
  const __nv_bfloat16* wmod = (const __nv_bfloat16*)d_in[10];
  static bool attr_done = false;
  static CUtensorMap tm_wmod, tm_wq;
  static const void* tm_src[2] = {nullptr, nullptr};
  if (!attr_done) {
    cudaFuncSetAttribute(fused_kernel, cudaFuncAttributeMaxDynamicSharedMemorySize, kSmemBytes);
    attr_done = true;
  }
  if (tm_src[0] != (const void*)wmod || tm_src[1] != (const void*)wq) {
    typedef CUresult (*EncodeFn)(CUtensorMap*, CUtensorMapDataType, cuuint32_t, void*, const cuuint64_t*,
                                 const cuuint64_t*, const cuuint32_t*, const cuuint32_t*, CUtensorMapInterleave,
                                 CUtensorMapSwizzle, CUtensorMapL2promotion, CUtensorMapFloatOOBfill);
    void* fn = nullptr;
    cudaDriverEntryPointQueryResult qres;
    cudaGetDriverEntryPoint("cuTensorMapEncodeTiled", &fn, cudaEnableDefault, &qres);
    const cuuint32_t estr[2] = {1, 1};
    {
      const cuuint64_t dims[2] = {6 * kD, kD}, strides[1] = {6 * kD * 2};
      const cuuint32_t box[2] = {32, 128};
      ((EncodeFn)fn)(&tm_wmod, CU_TENSOR_MAP_DATA_TYPE_BFLOAT16, 2, (void*)wmod, dims, strides, box, estr,
                     CU_TENSOR_MAP_INTERLEAVE_NONE, CU_TENSOR_MAP_SWIZZLE_64B, CU_TENSOR_MAP_L2_PROMOTION_L2_128B,
                     CU_TENSOR_MAP_FLOAT_OOB_FILL_NONE);
    }
    {
      const cuuint64_t dims[2] = {kH * kDH, kD}, strides[1] = {kH * kDH * 2};
      const cuuint32_t box[2] = {64, 128};
      ((EncodeFn)fn)(&tm_wq, CU_TENSOR_MAP_DATA_TYPE_BFLOAT16, 2, (void*)wq, dims, strides, box, estr,
                     CU_TENSOR_MAP_INTERLEAVE_NONE, CU_TENSOR_MAP_SWIZZLE_128B, CU_TENSOR_MAP_L2_PROMOTION_L2_128B,
                     CU_TENSOR_MAP_FLOAT_OOB_FILL_NONE);
    }
    tm_src[0] = wmod; tm_src[1] = wq;
  }
  fused_kernel<<<kNCTA, kThreads, kSmemBytes>>>(x, kc, vc, wo, wg, wu, wd, cv, tm_wmod, tm_wq, (__nv_bfloat16*)d_out);
}
```
